```python
import torch

def _softmax(x, axis=-1):
    return torch.softmax(x, dim=axis)
def _gelu(x):
    return torch.nn.functional.gelu(x, approximate="tanh")
def _silu(x):
    return torch.nn.functional.silu(x)
def _sigmoid(x):
    return torch.sigmoid(x)
def _layernorm(x, axis=-1, eps=1e-5):
    m = x.mean(dim=axis, keepdim=True)
    v = x.var(dim=axis, keepdim=True, unbiased=False)
    return (x - m) / torch.sqrt(v + eps)
def _scatter_add(tgt, idx, src, axis=0):
    return tgt.clone().index_add_(axis, idx, src)
def _segment_sum(src, seg, n):
    out = torch.zeros((n,) + src.shape[1:], dtype=src.dtype)
    return out.index_add_(0, seg, src)
def _pad(x, pw):
    flat = tuple(v for pair in reversed(pw) for v in pair)
    return torch.nn.functional.pad(x, flat)

kernel_name = 'concat_heads__linear_kernel_hedgehog__ssm_conv_s5__prompt'

def setup_inputs():

    _w = (lambda a: (lambda t: t.to(torch.bfloat16) if t.is_floating_point() else t)(torch.as_tensor(a)))
    def _A_setup():
        B, S, D, H = 1, 2048, 1024, 32
        Dh = D // H
        return {
            "x": _w((lambda *s: torch.randn(*s, dtype=torch.bfloat16) * 0.4)(B, S, D)),
            "wqkv": _w((lambda *s: torch.randn(*s, dtype=torch.bfloat16) * 0.4)(D, 3 * D)),
            "w_phi": _w((lambda *s: torch.randn(*s, dtype=torch.bfloat16) * 0.4)(H, Dh, Dh) * (Dh ** -0.5)),
            "wo": _w((lambda *s: torch.randn(*s, dtype=torch.bfloat16) * 0.05)(D, D)),
        }
    _A_in = _A_setup()

    def _B_setup():
        B, S, D = 1, 2048, 1024
        P = D
        Lambda_re = -0.5 * (lambda _x: torch.exp(torch.as_tensor(_x)))((lambda *s: torch.randn(*s, dtype=torch.bfloat16) * 0.8)(P))
        Lambda_im = (lambda *s: torch.randn(*s, dtype=torch.bfloat16) * 0.8)(P) * 1.0
        B_re = (lambda *s: torch.randn(*s, dtype=torch.bfloat16) * 0.8)(P, D) * (D ** -0.5)
        B_im = (lambda *s: torch.randn(*s, dtype=torch.bfloat16) * 0.8)(P, D) * (D ** -0.5)
        C_re = (lambda *s: torch.randn(*s, dtype=torch.bfloat16) * 0.8)(D, P) * (P ** -0.5)
        C_im = (lambda *s: torch.randn(*s, dtype=torch.bfloat16) * 0.8)(D, P) * (P ** -0.5)
        log_dt = (lambda *s: torch.randn(*s, dtype=torch.bfloat16) * 0.8)(P) * 0.3 - 2.0
        Dskip = (lambda *s: torch.randn(*s, dtype=torch.bfloat16) * 0.8)(D)
        return {
            "x": _w((lambda *s: torch.randn(*s, dtype=torch.bfloat16) * 0.05)(B, S, D)),
            "Lambda_re": _w(Lambda_re),
            "Lambda_im": _w(Lambda_im),
            "B_re": _w(B_re),
            "B_im": _w(B_im),
            "C_re": _w(C_re),
            "C_im": _w(C_im),
            "log_dt": _w(log_dt),
            "Dskip": _w(Dskip),
        }
    _B_in = _B_setup()

    return {
        "A_x": _A_in["x"],
        "A_wqkv": _A_in["wqkv"],
        "A_w_phi": _A_in["w_phi"],
        "A_wo": _A_in["wo"],
        "B_x": _B_in["x"],
        "B_Lambda_re": _B_in["Lambda_re"],
        "B_Lambda_im": _B_in["Lambda_im"],
        "B_B_re": _B_in["B_re"],
        "B_B_im": _B_in["B_im"],
        "B_C_re": _B_in["C_re"],
        "B_C_im": _B_in["C_im"],
        "B_log_dt": _B_in["log_dt"],
        "B_Dskip": _B_in["Dskip"],
    }

def reference(A_x, A_wqkv, A_w_phi, A_wo, B_x, B_Lambda_re, B_Lambda_im, B_B_re, B_B_im, B_C_re, B_C_im, B_log_dt, B_Dskip):
    def _A_ref(x, wqkv, w_phi, wo):
        B, S, D = x.shape
        H = 32; Dh = D // H
        qkv = (lambda x, *d: x.permute(*d))((x @ wqkv).reshape(B, S, 3, H, Dh), 2, 0, 3, 1, 4)
        q, k, v = qkv[0], qkv[1], qkv[2]
        pq = torch.einsum("bhsd,hdf->bhsf", q, w_phi)
        pk = torch.einsum("bhsd,hdf->bhsf", k, w_phi)
        phi_q = torch.concatenate([_softmax(pq, axis=-1), _softmax(-pq, axis=-1)], axis=-1)
        phi_k = torch.concatenate([_softmax(pk, axis=-1), _softmax(-pk, axis=-1)], axis=-1)
        kv = torch.einsum("bhsf,bhsd->bhfd", phi_k, v)
        z  = torch.einsum("bhsf->bhf", phi_k)
        num = torch.einsum("bhqf,bhfd->bhqd", phi_q, kv)
        den = torch.einsum("bhqf,bhf->bhq", phi_q, z)[..., None] + 1e-6
        o = num / den
        return (lambda x, *d: x.permute(*d))(o, 0, 2, 1, 3).reshape(B, S, D) @ wo

    def _B_ref(x, Lambda_re, Lambda_im, B_re, B_im, C_re, C_im, log_dt, Dskip):
        Bsz, L, H = x.shape
        Lam = Lambda_re + 1j * Lambda_im
        Bmat = B_re + 1j * B_im
        Cmat = C_re + 1j * C_im
        dt = torch.exp(log_dt)
        Lam_bar = torch.exp(dt * Lam)
        B_bar = ((Lam_bar - 1.0) / Lam)[:, None] * Bmat
        Bu = torch.einsum("bld,pd->blp", x + 0j, B_bar)
        h = torch.zeros_like(Bu[:, 0, :])
        hs = []
        for t in range(L):
            h = Lam_bar[None, :] * h + Bu[:, t, :]
            hs.append(h)
        hseq = torch.stack(hs, 1)
        y = 2.0 * torch.einsum("blp,dp->bld", hseq, Cmat).real + x * Dskip[None, None, :]
        return y

    a = _A_ref(A_x, A_wqkv, A_w_phi, A_wo)
    b = _B_ref(B_x, B_Lambda_re, B_Lambda_im, B_B_re, B_B_im, B_C_re, B_C_im, B_log_dt, B_Dskip)
    return torch.concatenate([a, b], axis=-1)
```

```cpp
#include <cuda_runtime.h>
#include <cuda_bf16.h>
#include <cuda.h>
#include <stdint.h>

namespace {

constexpr int SEQ = 2048;
constexpr int DM = 1024;
#define NSTAGES 5
constexpr int STAGES = NSTAGES;
constexpr int STAGE_BYTES = 32768;
constexpr int OFF_EB = 5 * STAGE_BYTES;
constexpr int OFF_PHI = OFF_EB;
constexpr int OFF_V = OFF_EB + 32768;
constexpr int OFF_WPHI = OFF_EB + 53248;
constexpr int OFF_ONES = OFF_EB + 61440;
constexpr int OFF_BAR = OFF_EB + 62464;
constexpr int SMEM_BYTES = OFF_BAR + 256 + 1024;
constexpr int B_EMPTY = 64, B_ORD = 128, B_EBF = 144, B_WPHI = 152, B_EPOCH = 160, B_KVX = 168  , B_E3 = 184, B_EPOCHV = 192;

constexpr int KVW = 40;

struct Params {
  CUtensorMap tmXB;
  CUtensorMap tmBre, tmBim;
  CUtensorMap tmXA;
  CUtensorMap tmWqkv;
  CUtensorMap tmWphi;
  CUtensorMap tmHT;
  CUtensorMap tmCre, tmCim;
  CUtensorMap tmO;
  CUtensorMap tmWo;
  const __nv_bfloat16* xB;
  const __nv_bfloat16* lam_re;
  const __nv_bfloat16* lam_im;
  const __nv_bfloat16* log_dt;
  const __nv_bfloat16* dskip;
  float* out;
};

__device__ __nv_bfloat16 g_HT[2048 * 2048];
__device__ __nv_bfloat16 g_O[SEQ * DM];
__device__ float g_kv[32 * 64 * KVW];
__device__ uint4 g_E[16 * 16 * 64];
struct Flags {
  unsigned ticket;   unsigned pad0[31];
  unsigned zero_cnt; unsigned pad1[31];
  unsigned hcnt[16 * 8];
  unsigned kvcnt[16 * 8];
  unsigned ocnt[16 * 8];
};
__device__ Flags g_flags;
#define TSTAMP(i)

__device__ unsigned g_abort;
__device__ __forceinline__ bool give_up(unsigned spins, unsigned limit) {
  if ((spins & 255u) != 0) return false;
  if (*(volatile unsigned*)&g_abort) return true;
  if (spins > limit) { *(volatile unsigned*)&g_abort = 1u; return true; }
  return false;
}
__device__ __forceinline__ uint32_t smem_u32(const void* p) { return (uint32_t)__cvta_generic_to_shared(p); }
__device__ __forceinline__ void mbar_init(uint32_t bar, uint32_t count) {
  asm volatile("mbarrier.init.shared::cta.b64 [%0], %1;" ::"r"(bar), "r"(count));
}
__device__ __forceinline__ void mbar_expect_tx(uint32_t bar, uint32_t bytes) {
  asm volatile("mbarrier.arrive.expect_tx.shared::cta.b64 _, [%0], %1;" ::"r"(bar), "r"(bytes) : "memory");
}
__device__ __forceinline__ void mbar_arrive(uint32_t bar) {
  asm volatile("mbarrier.arrive.shared::cta.b64 _, [%0];" ::"r"(bar) : "memory");
}
__device__ __forceinline__ void mbar_arrive_cluster(uint32_t bar, uint32_t cta) {
  asm volatile("{\n.reg .b32 ra;\nmapa.shared::cluster.u32 ra, %0, %1;\nmbarrier.arrive.shared::cluster.b64 _, [ra];\n}" ::"r"(bar), "r"(cta) : "memory");
}
__device__ __forceinline__ bool mbar_try(uint32_t bar, uint32_t parity) {
  uint32_t ok;
  asm volatile("{\n.reg .pred p;\nmbarrier.try_wait.parity.shared::cta.b64 p, [%1], %2;\nselp.u32 %0, 1, 0, p;\n}" : "=r"(ok) : "r"(bar), "r"(parity) : "memory");
  return ok != 0;
}
__device__ __forceinline__ void mbar_wait(uint32_t bar, uint32_t parity) {
  if (mbar_try(bar, parity)) return;
  uint32_t spins = 0;
  while (!mbar_try(bar, parity)) {
    if (give_up(++spins, 1u << 21)) break;
  }
}
__device__ __forceinline__ unsigned ld_relaxed(const unsigned* p) {
  unsigned v;
  asm volatile("ld.relaxed.gpu.global.u32 %0, [%1];" : "=r"(v) : "l"(p) : "memory");
  return v;
}
__device__ __forceinline__ void wait_ge(const unsigned* p, unsigned target) {
  unsigned spins = 0;
  while ((int)(ld_relaxed(p) - target) < 0) {
    __nanosleep(128);
    if (give_up(++spins, 1u << 20)) break;
  }
}
__device__ __forceinline__ void red_release_add(unsigned* p, unsigned v) {
  asm volatile("red.release.gpu.global.add.u32 [%0], %1;" ::"l"(p), "r"(v) : "memory");
}
__device__ __forceinline__ void red_relaxed_add(unsigned* p, unsigned v) {
  asm volatile("red.relaxed.gpu.global.add.u32 [%0], %1;" ::"l"(p), "r"(v) : "memory");
}
__device__ __forceinline__ void st_tagged(uint4* p, float a, float b, unsigned tag) {
  const unsigned long long w0 = ((unsigned long long)tag << 32) | __float_as_uint(a);
  const unsigned long long w1 = ((unsigned long long)tag << 32) | __float_as_uint(b);
  asm volatile("st.relaxed.gpu.global.v2.b64 [%0], {%1, %2};" ::"l"(p), "l"(w0), "l"(w1) : "memory");
}
__device__ __forceinline__ bool ld_tagged(const uint4* p, float& a, float& b, unsigned tag) {
  unsigned long long w0, w1;
  asm volatile("ld.relaxed.gpu.global.v2.b64 {%0, %1}, [%2];" : "=l"(w0), "=l"(w1) : "l"(p) : "memory");
  a = __uint_as_float((unsigned)w0);
  b = __uint_as_float((unsigned)w1);
  return (unsigned)(w0 >> 32) == tag && (unsigned)(w1 >> 32) == tag;
}
__device__ __forceinline__ void bulk_commit() { asm volatile("cp.async.bulk.commit_group;" ::: "memory"); }
__device__ __forceinline__ void bulk_wait_all() { asm volatile("cp.async.bulk.wait_group 0;" ::: "memory"); }
__device__ __forceinline__ void bulk_reduce_f32(float* dst, uint32_t src, uint32_t bytes) {
  asm volatile("cp.reduce.async.bulk.global.shared::cta.bulk_group.add.f32 [%0], [%1], %2;" ::"l"(dst), "r"(src), "r"(bytes) : "memory");
}
__device__ __forceinline__ void tma_store_3d(const CUtensorMap* tm, uint32_t src, int c0, int c1, int c2) {
  asm volatile("cp.async.bulk.tensor.3d.global.shared::cta.bulk_group [%0, {%2, %3, %4}], [%1];"
               ::"l"(tm), "r"(src), "r"(c0), "r"(c1), "r"(c2) : "memory");
}
__device__ __forceinline__ void fence_gpu() { asm volatile("fence.acq_rel.gpu;" ::: "memory"); }
__device__ __forceinline__ void fence_async_all() { asm volatile("fence.proxy.async;" ::: "memory"); }
__device__ __forceinline__ void fence_async_smem() { asm volatile("fence.proxy.async.shared::cta;" ::: "memory"); }
__device__ __forceinline__ void red_add_v2(float* p, float a, float b) {
  asm volatile("red.global.add.v2.f32 [%0], {%1, %2};" ::"l"(p), "f"(a), "f"(b) : "memory");
}
__device__ __forceinline__ void tma_2d(uint32_t dst, const CUtensorMap* tm, int c0, int c1, uint32_t bar) {
  asm volatile("cp.async.bulk.tensor.2d.shared::cluster.global.mbarrier::complete_tx::bytes [%0], [%1, {%3, %4}], [%2];"
               ::"r"(dst), "l"(tm), "r"(bar), "r"(c0), "r"(c1) : "memory");
}
__device__ __forceinline__ void tma_3d(uint32_t dst, const CUtensorMap* tm, int c0, int c1, int c2, uint32_t bar) {
  asm volatile("cp.async.bulk.tensor.3d.shared::cluster.global.mbarrier::complete_tx::bytes [%0], [%1, {%3, %4, %5}], [%2];"
               ::"r"(dst), "l"(tm), "r"(bar), "r"(c0), "r"(c1), "r"(c2) : "memory");
}
__device__ __forceinline__ void tma_5d(uint32_t dst, const CUtensorMap* tm, int c0, int c1, int c2, int c3, int c4, uint32_t bar) {
  asm volatile("cp.async.bulk.tensor.5d.shared::cluster.global.mbarrier::complete_tx::bytes [%0], [%1, {%3, %4, %5, %6, %7}], [%2];"
               ::"r"(dst), "l"(tm), "r"(bar), "r"(c0), "r"(c1), "r"(c2), "r"(c3), "r"(c4) : "memory");
}
__device__ __forceinline__ void tma_2d_mc(uint32_t dst, const CUtensorMap* tm, int c0, int c1, uint32_t bar) {
  asm volatile("cp.async.bulk.tensor.2d.shared::cluster.global.mbarrier::complete_tx::bytes.multicast::cluster [%0], [%1, {%3, %4}], [%2], %5;"
               ::"r"(dst), "l"(tm), "r"(bar), "r"(c0), "r"(c1), "h"((uint16_t)3) : "memory");
}
__device__ __forceinline__ void tma_store_2d(const CUtensorMap* tm, uint32_t src, int c0, int c1) {
  asm volatile("cp.async.bulk.tensor.2d.global.shared::cta.bulk_group [%0, {%2, %3}], [%1];"
               ::"l"(tm), "r"(src), "r"(c0), "r"(c1) : "memory");
}
__device__ __forceinline__ void prefetch_tm(const CUtensorMap* tm) {
  asm volatile("prefetch.tensormap [%0];" ::"l"(tm) : "memory");
}
__device__ __forceinline__ void wgmma_fence() { asm volatile("wgmma.fence.sync.aligned;" ::: "memory"); }
__device__ __forceinline__ void wgmma_commit() { asm volatile("wgmma.commit_group.sync.aligned;" ::: "memory"); }
template <int N> __device__ __forceinline__ void wgmma_wait() { asm volatile("wgmma.wait_group.sync.aligned %0;" ::"n"(N) : "memory"); }
__device__ __forceinline__ void wg_bar(int id) {
  if (id == 1) asm volatile("bar.sync 1, 128;" ::: "memory");
  else asm volatile("bar.sync 2, 128;" ::: "memory");
}
template <int R> __device__ __forceinline__ void reg_alloc() { asm volatile("setmaxnreg.inc.sync.aligned.u32 %0;" ::"n"(R)); }
template <int R> __device__ __forceinline__ void reg_dealloc() { asm volatile("setmaxnreg.dec.sync.aligned.u32 %0;" ::"n"(R)); }

__device__ __forceinline__ uint64_t make_desc(uint32_t saddr, uint32_t lbo_bytes, uint32_t sbo_bytes, uint32_t layout) {
  uint64_t d = (uint64_t)((saddr & 0x3FFFF) >> 4);
  d |= (uint64_t)((lbo_bytes & 0x3FFFF) >> 4) << 16;
  d |= (uint64_t)((sbo_bytes & 0x3FFFF) >> 4) << 32;
  d |= (uint64_t)layout << 62;
  return d;
}
__device__ __forceinline__ uint64_t desc128(uint32_t lo) { return ((uint64_t)0x40000040u << 32) | lo; }
__device__ __forceinline__ uint32_t pack_bf16(float lo, float hi) {
  uint32_t r;
  asm("cvt.rn.bf16x2.f32 %0, %1, %2;" : "=r"(r) : "f"(hi), "f"(lo));
  return r;
}
__device__ __forceinline__ float ex2(float x) { float y; asm("ex2.approx.ftz.f32 %0, %1;" : "=f"(y) : "f"(x)); return y; }
__device__ __forceinline__ float rcp(float x) { float y; asm("rcp.approx.ftz.f32 %0, %1;" : "=f"(y) : "f"(x)); return y; }
__device__ __forceinline__ void stmatrix_x4(uint32_t addr, uint32_t r0, uint32_t r1, uint32_t r2, uint32_t r3) {
  asm volatile("stmatrix.sync.aligned.m8n8.x4.shared.b16 [%0], {%1, %2, %3, %4};" ::"r"(addr), "r"(r0), "r"(r1), "r"(r2), "r"(r3) : "memory");
}
template <int N> __device__ __forceinline__ void fence_regs(float (&d)[N]) {
#pragma unroll
  for (int i = 0; i < N; i++) asm volatile("" : "+f"(d[i])::"memory");
}

template <int TA, int TB>
__device__ __forceinline__ void wgmma_m64n128k16_ss(float (&d)[64], uint64_t descA, uint64_t descB, int scaleD) {
  asm volatile("{\n.reg .pred p;\nsetp.ne.b32 p, %66, 0;\n"
    "wgmma.mma_async.sync.aligned.m64n128k16.f32.bf16.bf16 "
    "{%0, %1, %2, %3, %4, %5, %6, %7, %8, %9, %10, %11, %12, %13, %14, %15, %16, %17, %18, %19, %20, %21, %22, %23, %24, %25, %26, %27, %28, %29, %30, %31, %32, %33, %34, %35, %36, %37, %38, %39, %40, %41, %42, %43, %44, %45, %46, %47, %48, %49, %50, %51, %52, %53, %54, %55, %56, %57, %58, %59, %60, %61, %62, %63}, "
    "%64, %65, p, 1, 1, %67, %68;\n}\n"
    : "+f"(d[0]), "+f"(d[1]), "+f"(d[2]), "+f"(d[3]), "+f"(d[4]), "+f"(d[5]), "+f"(d[6]), "+f"(d[7]), "+f"(d[8]), "+f"(d[9]), "+f"(d[10]), "+f"(d[11]), "+f"(d[12]), "+f"(d[13]), "+f"(d[14]), "+f"(d[15]), "+f"(d[16]), "+f"(d[17]), "+f"(d[18]), "+f"(d[19]), "+f"(d[20]), "+f"(d[21]), "+f"(d[22]), "+f"(d[23]), "+f"(d[24]), "+f"(d[25]), "+f"(d[26]), "+f"(d[27]), "+f"(d[28]), "+f"(d[29]), "+f"(d[30]), "+f"(d[31]), "+f"(d[32]), "+f"(d[33]), "+f"(d[34]), "+f"(d[35]), "+f"(d[36]), "+f"(d[37]), "+f"(d[38]), "+f"(d[39]), "+f"(d[40]), "+f"(d[41]), "+f"(d[42]), "+f"(d[43]), "+f"(d[44]), "+f"(d[45]), "+f"(d[46]), "+f"(d[47]), "+f"(d[48]), "+f"(d[49]), "+f"(d[50]), "+f"(d[51]), "+f"(d[52]), "+f"(d[53]), "+f"(d[54]), "+f"(d[55]), "+f"(d[56]), "+f"(d[57]), "+f"(d[58]), "+f"(d[59]), "+f"(d[60]), "+f"(d[61]), "+f"(d[62]), "+f"(d[63])
    : "l"(descA), "l"(descB), "r"(scaleD), "n"(TA), "n"(TB));
}

template <int TB>
__device__ __forceinline__ void wgmma_m64n32k16_rs(float (&d)[16], uint32_t a0, uint32_t a1, uint32_t a2, uint32_t a3, uint64_t descB, int scaleD) {
  asm volatile("{\n.reg .pred p;\nsetp.ne.b32 p, %21, 0;\n"
    "wgmma.mma_async.sync.aligned.m64n32k16.f32.bf16.bf16 "
    "{%0, %1, %2, %3, %4, %5, %6, %7, %8, %9, %10, %11, %12, %13, %14, %15}, "
    "{%16, %17, %18, %19}, %20, p, 1, 1, %22;\n}\n"
    : "+f"(d[0]), "+f"(d[1]), "+f"(d[2]), "+f"(d[3]), "+f"(d[4]), "+f"(d[5]), "+f"(d[6]), "+f"(d[7]), "+f"(d[8]), "+f"(d[9]), "+f"(d[10]), "+f"(d[11]), "+f"(d[12]), "+f"(d[13]), "+f"(d[14]), "+f"(d[15])
    : "r"(a0), "r"(a1), "r"(a2), "r"(a3), "l"(descB), "r"(scaleD), "n"(TB));
}

template <int TB>
__device__ __forceinline__ void wgmma_m64n40k16_rs(float (&d)[20], uint32_t a0, uint32_t a1, uint32_t a2, uint32_t a3, uint64_t descB, int scaleD) {
  asm volatile("{\n.reg .pred p;\nsetp.ne.b32 p, %25, 0;\n"
    "wgmma.mma_async.sync.aligned.m64n40k16.f32.bf16.bf16 "
    "{%0, %1, %2, %3, %4, %5, %6, %7, %8, %9, %10, %11, %12, %13, %14, %15, %16, %17, %18, %19}, "
    "{%20, %21, %22, %23}, %24, p, 1, 1, %26;\n}\n"
    : "+f"(d[0]), "+f"(d[1]), "+f"(d[2]), "+f"(d[3]), "+f"(d[4]), "+f"(d[5]), "+f"(d[6]), "+f"(d[7]), "+f"(d[8]), "+f"(d[9]), "+f"(d[10]), "+f"(d[11]), "+f"(d[12]), "+f"(d[13]), "+f"(d[14]), "+f"(d[15]), "+f"(d[16]), "+f"(d[17]), "+f"(d[18]), "+f"(d[19])
    : "r"(a0), "r"(a1), "r"(a2), "r"(a3), "l"(descB), "r"(scaleD), "n"(TB));
}

template <int TA, int TB>
__device__ __forceinline__ void wgmma_m64n40k16_ss(float (&d)[20], uint64_t descA, uint64_t descB, int scaleD) {
  asm volatile("{\n.reg .pred p;\nsetp.ne.b32 p, %22, 0;\n"
    "wgmma.mma_async.sync.aligned.m64n40k16.f32.bf16.bf16 "
    "{%0, %1, %2, %3, %4, %5, %6, %7, %8, %9, %10, %11, %12, %13, %14, %15, %16, %17, %18, %19}, "
    "%20, %21, p, 1, 1, %23, %24;\n}\n"
    : "+f"(d[0]), "+f"(d[1]), "+f"(d[2]), "+f"(d[3]), "+f"(d[4]), "+f"(d[5]), "+f"(d[6]), "+f"(d[7]), "+f"(d[8]), "+f"(d[9]), "+f"(d[10]), "+f"(d[11]), "+f"(d[12]), "+f"(d[13]), "+f"(d[14]), "+f"(d[15]), "+f"(d[16]), "+f"(d[17]), "+f"(d[18]), "+f"(d[19])
    : "l"(descA), "l"(descB), "r"(scaleD), "n"(TA), "n"(TB));
}

template <int TA, int TB>
__device__ __forceinline__ void wgmma_m64n32k16_ss(float (&d)[16], uint64_t descA, uint64_t descB, int scaleD) {
  asm volatile("{\n.reg .pred p;\nsetp.ne.b32 p, %18, 0;\n"
    "wgmma.mma_async.sync.aligned.m64n32k16.f32.bf16.bf16 "
    "{%0, %1, %2, %3, %4, %5, %6, %7, %8, %9, %10, %11, %12, %13, %14, %15}, "
    "%16, %17, p, 1, 1, %19, %20;\n}\n"
    : "+f"(d[0]), "+f"(d[1]), "+f"(d[2]), "+f"(d[3]), "+f"(d[4]), "+f"(d[5]), "+f"(d[6]), "+f"(d[7]), "+f"(d[8]), "+f"(d[9]), "+f"(d[10]), "+f"(d[11]), "+f"(d[12]), "+f"(d[13]), "+f"(d[14]), "+f"(d[15])
    : "l"(descA), "l"(descB), "r"(scaleD), "n"(TA), "n"(TB));
}

template <int MODE>
__device__ __forceinline__ void mainloop(float (&acc0)[64], float (&acc1)[64], int it0, int nkb, uint32_t sbase, int cw,
                                         uint32_t ord_parity) {
  const uint32_t bars = sbase + OFF_BAR;
  const int lane = threadIdx.x & 31;
  int stage = it0 % STAGES;
  uint32_t phase = (it0 / STAGES) & 1;
#pragma unroll
  for (int i = 0; i < 64; i++) { acc0[i] = 0.f; acc1[i] = 0.f; }
  mbar_wait(bars + B_ORD + 8 * cw, ord_parity);
  int prev = 0;
  for (int kb = 0; kb < nkb; kb++) {
    mbar_wait(bars + 8 * stage, phase);
    if (kb == nkb - 1 && (threadIdx.x & 127) == 0) mbar_arrive(bars + B_ORD + 8 * (cw ^ 1));
    const uint32_t lo = ((sbase & 0x3FFFFu) + stage * STAGE_BYTES) >> 4;
    const uint32_t loK = lo | (1u << 16), loM = lo | (512u << 16);
    wgmma_fence();
#pragma unroll
    for (int k = 0; k < 4; k++) {
      if (MODE == 0) {
        const uint64_t dx = desc128(loK + 1024 + 2 * k);
        wgmma_m64n128k16_ss<0, 0>(acc0, desc128(loK + 2 * k), dx, 1);
        wgmma_m64n128k16_ss<0, 0>(acc1, desc128(loK + 512 + 2 * k), dx, 1);
      } else if (MODE == 1) {
        const uint64_t dw = desc128(loM + 128 * k);
        wgmma_m64n128k16_ss<0, 1>(acc0, desc128(loK + 1024 + 2 * k), dw, 1);
        wgmma_m64n128k16_ss<0, 1>(acc1, desc128(loK + 1536 + 2 * k), dw, 1);
      } else {
        const uint64_t dw = desc128(loK + 2 * k);
        wgmma_m64n128k16_ss<1, 0>(acc0, desc128(loM + 1024 + 128 * k), dw, 1);
        wgmma_m64n128k16_ss<1, 0>(acc1, desc128(loM + 1536 + 128 * k), dw, 1);
      }
    }
    wgmma_commit();
    wgmma_wait<1>();
    if (kb > 0 && lane < 2) mbar_arrive_cluster(bars + B_EMPTY + 8 * prev, lane);
    prev = stage;
    if (++stage == STAGES) { stage = 0; phase ^= 1; }
  }
  wgmma_wait<0>();
  if (lane < 2) mbar_arrive_cluster(bars + B_EMPTY + 8 * prev, lane);
  fence_regs(acc0);
  fence_regs(acc1);
}

__device__ __forceinline__ void dual_softmax(const float (&p)[16], uint32_t (&pos)[8], uint32_t (&neg)[8]) {
  constexpr float L2E = 1.4426950408889634f;
  float mx0 = p[0], mn0 = p[0], mx1 = p[2], mn1 = p[2];
#pragma unroll
  for (int j = 0; j < 4; j++) {
    mx0 = fmaxf(mx0, fmaxf(p[4 * j], p[4 * j + 1])); mn0 = fminf(mn0, fminf(p[4 * j], p[4 * j + 1]));
    mx1 = fmaxf(mx1, fmaxf(p[4 * j + 2], p[4 * j + 3])); mn1 = fminf(mn1, fminf(p[4 * j + 2], p[4 * j + 3]));
  }
#pragma unroll
  for (int o = 1; o <= 2; o <<= 1) {
    mx0 = fmaxf(mx0, __shfl_xor_sync(0xffffffffu, mx0, o)); mn0 = fminf(mn0, __shfl_xor_sync(0xffffffffu, mn0, o));
    mx1 = fmaxf(mx1, __shfl_xor_sync(0xffffffffu, mx1, o)); mn1 = fminf(mn1, __shfl_xor_sync(0xffffffffu, mn1, o));
  }
  const float a0 = -mx0 * L2E, b0 = mn0 * L2E, a1 = -mx1 * L2E, b1 = mn1 * L2E;
  float ep[16], en[16];
  float sp0 = 0.f, sn0 = 0.f, sp1 = 0.f, sn1 = 0.f;
#pragma unroll
  for (int j = 0; j < 4; j++) {
#pragma unroll
    for (int e = 0; e < 2; e++) {
      const float x0 = p[4 * j + e], x1 = p[4 * j + 2 + e];
      ep[4 * j + e] = ex2(fmaf(x0, L2E, a0)); en[4 * j + e] = ex2(fmaf(x0, -L2E, b0));
      ep[4 * j + 2 + e] = ex2(fmaf(x1, L2E, a1)); en[4 * j + 2 + e] = ex2(fmaf(x1, -L2E, b1));
      sp0 += ep[4 * j + e]; sn0 += en[4 * j + e];
      sp1 += ep[4 * j + 2 + e]; sn1 += en[4 * j + 2 + e];
    }
  }
#pragma unroll
  for (int o = 1; o <= 2; o <<= 1) {
    sp0 += __shfl_xor_sync(0xffffffffu, sp0, o); sn0 += __shfl_xor_sync(0xffffffffu, sn0, o);
    sp1 += __shfl_xor_sync(0xffffffffu, sp1, o); sn1 += __shfl_xor_sync(0xffffffffu, sn1, o);
  }
  const float rp0 = rcp(sp0), rn0 = rcp(sn0), rp1 = rcp(sp1), rn1 = rcp(sn1);
#pragma unroll
  for (int j = 0; j < 4; j++) {
    pos[2 * j] = pack_bf16(ep[4 * j] * rp0, ep[4 * j + 1] * rp0);
    pos[2 * j + 1] = pack_bf16(ep[4 * j + 2] * rp1, ep[4 * j + 3] * rp1);
    neg[2 * j] = pack_bf16(en[4 * j] * rn0, en[4 * j + 1] * rn0);
    neg[2 * j + 1] = pack_bf16(en[4 * j + 2] * rn1, en[4 * j + 3] * rn1);
  }
}

struct cplx { float r, i; };
__device__ __forceinline__ cplx cmul(cplx a, cplx b) { return {a.r * b.r - a.i * b.i, a.r * b.i + a.i * b.r}; }
__device__ __forceinline__ cplx cfma(cplx a, cplx b, cplx c) {
  return {fmaf(a.r, b.r, fmaf(-a.i, b.i, c.r)), fmaf(a.r, b.i, fmaf(a.i, b.r, c.i))};
}
__device__ __forceinline__ cplx shfl_up_c(cplx v, int d) {
  return {__shfl_up_sync(0xffffffffu, v.r, d, 4), __shfl_up_sync(0xffffffffu, v.i, d, 4)};
}

struct ChanParams { cplx lam, c2; };

__device__ __forceinline__ ChanParams chan_params(const Params& prm, int p) {
  const float lr = __bfloat162float(prm.lam_re[p]), li = __bfloat162float(prm.lam_im[p]);
  const float dt = __bfloat162float(__float2bfloat16(expf(__bfloat162float(prm.log_dt[p]))));
  const float mag = expf(dt * lr);
  float sn, cs;
  sincosf(dt * li, &sn, &cs);
  ChanParams c;
  c.lam = {mag * cs, mag * sn};
  const float nr = c.lam.r - 1.0f, ni = c.lam.i;
  const float den = lr * lr + li * li;
  c.c2 = {2.0f * (nr * lr + ni * li) / den, 2.0f * (ni * lr - nr * li) / den};
  return c;
}

__device__ __forceinline__ void epi_bu(float (&are)[64], float (&aim)[64], const ChanParams (&cp)[2], const Params& prm,
                                       uint32_t sbase, int G, int chunk, int cw, unsigned epoch) {
  const int lane = threadIdx.x & 31, w = (threadIdx.x & 127) >> 5, q = lane & 3, r8 = lane >> 2;
  cplx E[2] = {{0.f, 0.f}, {0.f, 0.f}};
#pragma unroll
  for (int k8 = 0; k8 < 16; k8++)
#pragma unroll
    for (int e = 0; e < 2; e++)
#pragma unroll
      for (int c = 0; c < 2; c++) E[c] = cfma(cp[c].lam, E[c], cplx{are[4 * k8 + 2 * c + e], aim[4 * k8 + 2 * c + e]});
  TSTAMP(32 + 4 * (threadIdx.x >> 8));
  cplx L32[2], L128[2], prev[2];
#pragma unroll
  for (int c = 0; c < 2; c++) {
    cplx l = cp[c].lam;
#pragma unroll
    for (int s = 0; s < 5; s++) l = cmul(l, l);
    L32[c] = l;
    const cplx l64 = cmul(l, l);
    L128[c] = cmul(l64, l64);
    cplx t = shfl_up_c(E[c], 1);
    if (q >= 1) E[c] = cfma(L32[c], t, E[c]);
    t = shfl_up_c(E[c], 2);
    if (q >= 2) E[c] = cfma(l64, t, E[c]);
    prev[c] = shfl_up_c(E[c], 1);
    if (q == 0) prev[c] = {0.f, 0.f};
  }
  uint4* gE = g_E + (size_t)G * 16 * 64 + 16 * w + r8;
  if (q == 3) {
    st_tagged(gE + chunk * 64, E[0].r, E[0].i, epoch);
    st_tagged(gE + chunk * 64 + 8, E[1].r, E[1].i, epoch);
  }
  cplx V[2][4];
  {
    unsigned long long w0[8], w1[8];
    unsigned pending = 0;
#pragma unroll
    for (int i = 0; i < 8; i++) {
      w0[i] = 0ull; w1[i] = 0ull;
      if (chunk - 1 - 4 * q - (i & 3) >= 0) pending |= 1u << i;
    }
    unsigned spins = 0;
    if (chunk > 0) __nanosleep(300);
    while (true) {
#pragma unroll
      for (int i = 0; i < 8; i++)
        asm volatile("{\n.reg .pred p;\nsetp.ne.u32 p, %3, 0;\n@p ld.relaxed.gpu.global.v2.b64 {%0, %1}, [%2];\n}"
                     : "+l"(w0[i]), "+l"(w1[i]) : "l"(gE + (chunk - 1 - 4 * q - (i & 3)) * 64 + 8 * (i >> 2)), "r"(pending & (1u << i)) : "memory");
#pragma unroll
      for (int i = 0; i < 8; i++)
        if ((unsigned)(w0[i] >> 32) == epoch && (unsigned)(w1[i] >> 32) == epoch) pending &= ~(1u << i);
      if (__all_sync(0xffffffffu, pending == 0)) break;
      __nanosleep(150);
      if (give_up(++spins, 1u << 20)) break;
    }
#pragma unroll
    for (int i = 0; i < 8; i++) V[i >> 2][i & 3] = {__uint_as_float((unsigned)w0[i]), __uint_as_float((unsigned)w1[i])};
  }
  TSTAMP(33 + 4 * (threadIdx.x >> 8));
  cplx s[2];
#pragma unroll
  for (int c = 0; c < 2; c++) {
    cplx Pq = V[c][3];
#pragma unroll
    for (int jj = 2; jj >= 0; jj--) Pq = cfma(L128[c], Pq, V[c][jj]);
    const cplx l256 = cmul(L128[c], L128[c]);
    const cplx l512 = cmul(l256, l256);
    cplx F = {1.f, 0.f};
    cplx G32 = {1.f, 0.f};
    if (q >= 1) { F = l512; G32 = L32[c]; }
    if (q >= 2) { F = cmul(F, l512); G32 = cmul(G32, L32[c]); }
    if (q >= 3) { F = cmul(F, l512); G32 = cmul(G32, L32[c]); }
    Pq = cmul(Pq, F);
#pragma unroll
    for (int o = 1; o <= 2; o <<= 1) {
      Pq.r += __shfl_xor_sync(0xffffffffu, Pq.r, o);
      Pq.i += __shfl_xor_sync(0xffffffffu, Pq.i, o);
    }
    s[c] = cfma(G32, Pq, prev[c]);
  }
  TSTAMP(34 + 4 * (threadIdx.x >> 8));
  if (cw == 1) mbar_wait(sbase + OFF_BAR + B_EBF, 0);
#pragma unroll
  for (int qq = 0; qq < 4; qq++) {
    uint32_t ore[2][4], oim[2][4];
#pragma unroll
    for (int kk = 0; kk < 4; kk++) {
      const int k8 = 4 * qq + kk;
      float hr[2][2], hi[2][2];
#pragma unroll
      for (int e = 0; e < 2; e++)
#pragma unroll
        for (int c = 0; c < 2; c++) {
          s[c] = cfma(cp[c].lam, s[c], cplx{are[4 * k8 + 2 * c + e], aim[4 * k8 + 2 * c + e]});
          hr[c][e] = fmaf(cp[c].c2.r, s[c].r, -cp[c].c2.i * s[c].i);
          hi[c][e] = -fmaf(cp[c].c2.r, s[c].i, cp[c].c2.i * s[c].r);
        }
#pragma unroll
      for (int c = 0; c < 2; c++) {
        ore[c][kk] = pack_bf16(hr[c][0], hr[c][1]);
        oim[c][kk] = pack_bf16(hi[c][0], hi[c][1]);
      }
    }
#pragma unroll
    for (int c = 0; c < 2; c++) {
      const int row = 16 * w + r8 + 8 * c;
      const uint32_t addr = sbase + OFF_PHI + (qq >> 1) * 8192 + row * 128 + ((((qq & 1) * 4 + q) ^ (row & 7)) << 4);
      asm volatile("st.shared.v4.b32 [%0], {%1, %2, %3, %4};" ::"r"(addr), "r"(ore[c][0]), "r"(ore[c][1]), "r"(ore[c][2]), "r"(ore[c][3]) : "memory");
      asm volatile("st.shared.v4.b32 [%0], {%1, %2, %3, %4};" ::"r"(addr + 16384), "r"(oim[c][0]), "r"(oim[c][1]), "r"(oim[c][2]), "r"(oim[c][3]) : "memory");
    }
  }
  TSTAMP(35 + 4 * (threadIdx.x >> 8));
  fence_async_smem();
  wg_bar(1 + cw);
  if ((threadIdx.x & 127) == 0) {
    tma_store_3d(&prm.tmHT, sbase + OFF_PHI, 0, 64 * G, 2 * chunk);
    tma_store_3d(&prm.tmHT, sbase + OFF_PHI + 16384, 0, 1024 + 64 * G, 2 * chunk);
    bulk_commit();
    bulk_wait_all();
    red_relaxed_add(&g_flags.hcnt[chunk * 8], 1);
    mbar_arrive(sbase + OFF_BAR + B_EBF);
  }
}

__device__ __forceinline__ void epi_kv(float (&acc0)[64], float (&acc1)[64], uint32_t sbase, int hp, int wslot, int cw,
                                       unsigned epoch) {
  const int t = threadIdx.x & 127, lane = t & 31, w = t >> 5, q = lane & 3, r8 = lane >> 2;
  const int mi = lane >> 3, rin = lane & 7;
  uint32_t kf[2][2][8];
#pragma unroll
  for (int half = 0; half < 2; half++) {
    float (&a)[64] = half ? acc1 : acc0;
    const int row = half * 64 + w * 16 + (mi & 1) * 8 + rin;
#pragma unroll
    for (int hh = 0; hh < 2; hh++) {
#pragma unroll
      for (int jp = 0; jp < 2; jp++) {
        const int j = 8 + hh * 4 + jp * 2;
        const int chunk = jp * 2 + (mi >> 1);
        const uint32_t addr = sbase + OFF_V + hh * 8192 + row * 64 + ((chunk ^ ((row >> 1) & 3)) << 4);
        stmatrix_x4(addr, pack_bf16(a[4 * j], a[4 * j + 1]), pack_bf16(a[4 * j + 2], a[4 * j + 3]),
                    pack_bf16(a[4 * j + 4], a[4 * j + 5]), pack_bf16(a[4 * j + 6], a[4 * j + 7]));
      }
#pragma unroll
      for (int i = 0; i < 8; i++) kf[half][hh][i] = pack_bf16(a[16 * hh + 2 * i], a[16 * hh + 2 * i + 1]);
    }
  }
  TSTAMP(40 + 8 * cw);
  float pk[2][2][16];
  wgmma_fence();
#pragma unroll
  for (int hh = 0; hh < 2; hh++)
#pragma unroll
    for (int half = 0; half < 2; half++)
#pragma unroll
      for (int ks = 0; ks < 2; ks++)
        wgmma_m64n32k16_rs<1>(pk[half][hh], kf[half][hh][4 * ks], kf[half][hh][4 * ks + 1], kf[half][hh][4 * ks + 2],
                              kf[half][hh][4 * ks + 3],
                              make_desc(sbase + OFF_WPHI + (wslot + hh) * 2048 + ks * 1024, 512, 512, 2), ks);
  wgmma_commit();
  wgmma_wait<0>();
#pragma unroll
  for (int half = 0; half < 2; half++)
#pragma unroll
    for (int hh = 0; hh < 2; hh++) fence_regs(pk[half][hh]);

  TSTAMP(41 + 8 * cw);
  float kvacc[2][20];
#pragma unroll
  for (int hh = 0; hh < 2; hh++) {
#pragma unroll
    for (int half = 0; half < 2; half++) {
      uint32_t pos[8], neg[8];
      dual_softmax(pk[half][hh], pos, neg);
      const int row = half * 64 + w * 16 + (mi & 1) * 8 + rin;
      const uint32_t rb = sbase + OFF_PHI + hh * 16384 + row * 128;
#pragma unroll
      for (int jp = 0; jp < 2; jp++) {
        const int c0 = jp * 2 + (mi >> 1);
        stmatrix_x4(rb + ((c0 ^ rin) << 4), pos[4 * jp], pos[4 * jp + 1], pos[4 * jp + 2], pos[4 * jp + 3]);
        stmatrix_x4(rb + (((c0 + 4) ^ rin) << 4), neg[4 * jp], neg[4 * jp + 1], neg[4 * jp + 2], neg[4 * jp + 3]);
      }
    }
    fence_async_smem();
    wg_bar(1 + cw);
    wgmma_fence();
#pragma unroll
    for (int ks = 0; ks < 8; ks++) {
      const uint32_t vb = sbase + OFF_V + hh * 8192 + ks * 1024;
      wgmma_m64n40k16_ss<1, 1>(kvacc[hh], make_desc(sbase + OFF_PHI + hh * 16384 + ks * 2048, 1024, 1024, 1),
                               make_desc(vb, sbase + OFF_ONES - vb, 512, 2), ks);
    }
    wgmma_commit();
  }
  TSTAMP(42 + 8 * cw);
  wgmma_wait<0>();
  fence_regs(kvacc[0]);
  fence_regs(kvacc[1]);
  TSTAMP(43 + 8 * cw);
  wg_bar(1 + cw);
#pragma unroll
  for (int hh = 0; hh < 2; hh++) {
    const uint32_t dst = sbase + OFF_PHI + hh * 16384 + ((16 * w + r8) * KVW + 2 * q) * 4;
#pragma unroll
    for (int j = 0; j < 5; j++) {
      asm volatile("st.shared.v2.f32 [%0], {%1, %2};" ::"r"(dst + 32 * j), "f"(kvacc[hh][4 * j]), "f"(kvacc[hh][4 * j + 1]) : "memory");
      asm volatile("st.shared.v2.f32 [%0], {%1, %2};" ::"r"(dst + 8 * KVW * 4 + 32 * j), "f"(kvacc[hh][4 * j + 2]), "f"(kvacc[hh][4 * j + 3]) : "memory");
    }
  }
  fence_async_smem();
  wg_bar(1 + cw);
  TSTAMP(44 + 8 * cw);
  if (t == 0) {
    wait_ge(&g_flags.zero_cnt, 128u * epoch);
    bulk_reduce_f32(g_kv + (size_t)(2 * hp) * 64 * KVW, sbase + OFF_PHI, 64 * KVW * 4);
    bulk_reduce_f32(g_kv + (size_t)(2 * hp + 1) * 64 * KVW, sbase + OFF_PHI + 16384, 64 * KVW * 4);
    bulk_commit();
    bulk_wait_all();
    red_relaxed_add(&g_flags.kvcnt[hp * 8], 1);
    mbar_arrive(sbase + OFF_BAR + B_EBF);
    if (cw == 1) mbar_arrive(sbase + OFF_BAR + B_E3);
  }
  TSTAMP(45 + 8 * cw);
}

__device__ __forceinline__ void q_issue_pq(float (&pq)[16], uint32_t sbase, int item) {
  const int half = item & 1, hs = item >> 1;
  const uint32_t a = sbase + OFF_PHI + (hs >> 1) * 16384 + half * 8192 + (hs & 1) * 64;
  const uint32_t b = sbase + OFF_WPHI + hs * 2048;
  wgmma_fence();
  wgmma_m64n32k16_ss<0, 1>(pq, make_desc(a, 16, 1024, 1), make_desc(b, 512, 512, 2), 0);
  wgmma_m64n32k16_ss<0, 1>(pq, make_desc(a + 32, 16, 1024, 1), make_desc(b + 1024, 512, 512, 2), 1);
  wgmma_commit();
}
__device__ __forceinline__ void q_issue_num(float (&num)[20], const uint32_t (&pos)[8], const uint32_t (&neg)[8], uint32_t sbase, int item) {
  const uint32_t b = sbase + OFF_V + (item >> 1) * 5120;
  wgmma_fence();
  wgmma_m64n40k16_rs<1>(num, pos[0], pos[1], pos[2], pos[3], make_desc(b, 640, 128, 0), 0);
  wgmma_m64n40k16_rs<1>(num, pos[4], pos[5], pos[6], pos[7], make_desc(b + 1280, 640, 128, 0), 1);
  wgmma_m64n40k16_rs<1>(num, neg[0], neg[1], neg[2], neg[3], make_desc(b + 2560, 640, 128, 0), 1);
  wgmma_m64n40k16_rs<1>(num, neg[4], neg[5], neg[6], neg[7], make_desc(b + 3840, 640, 128, 0), 1);
  wgmma_commit();
}
__device__ __forceinline__ void q_store_o(const float (&num)[20], uint32_t sbase, int item) {
  const int lane = threadIdx.x & 31, w = (threadIdx.x & 127) >> 5, mi = lane >> 3, rin = lane & 7;
  const int half = item & 1, hs = item >> 1;
  const float d0 = __shfl_sync(0xffffffffu, num[16], lane & ~3), d1 = __shfl_sync(0xffffffffu, num[18], lane & ~3);
  const float i0 = __fdividef(1.0f, d0 + 1e-6f), i1 = __fdividef(1.0f, d1 + 1e-6f);
  const int row = half * 64 + w * 16 + (mi & 1) * 8 + rin;
  const uint32_t rb = sbase + OFF_PHI + (hs >> 1) * 16384 + row * 128;
#pragma unroll
  for (int jp = 0; jp < 2; jp++) {
    const int c0 = (hs & 1) * 4 + jp * 2 + (mi >> 1);
    stmatrix_x4(rb + ((c0 ^ rin) << 4), pack_bf16(num[8 * jp] * i0, num[8 * jp + 1] * i0),
                pack_bf16(num[8 * jp + 2] * i1, num[8 * jp + 3] * i1), pack_bf16(num[8 * jp + 4] * i0, num[8 * jp + 5] * i0),
                pack_bf16(num[8 * jp + 6] * i1, num[8 * jp + 7] * i1));
  }
}
__device__ __forceinline__ void epi_q(float (&acc0)[64], float (&acc1)[64], const Params& prm, uint32_t sbase, int g, int rb_idx) {
  const int t = threadIdx.x & 127, lane = t & 31, w = t >> 5;
  const int mi = lane >> 3, rin = lane & 7;
  {
    const int row = w * 16 + (mi & 1) * 8 + rin;
#pragma unroll
    for (int jp = 0; jp < 8; jp++) {
      const int j = 2 * jp, c0 = (j & 7) + (mi >> 1);
      const uint32_t addr = sbase + OFF_PHI + (j >> 3) * 16384 + row * 128 + ((c0 ^ rin) << 4);
      stmatrix_x4(addr, pack_bf16(acc0[4 * j], acc0[4 * j + 1]), pack_bf16(acc0[4 * j + 2], acc0[4 * j + 3]),
                  pack_bf16(acc0[4 * j + 4], acc0[4 * j + 5]), pack_bf16(acc0[4 * j + 6], acc0[4 * j + 7]));
      stmatrix_x4(addr + 8192, pack_bf16(acc1[4 * j], acc1[4 * j + 1]), pack_bf16(acc1[4 * j + 2], acc1[4 * j + 3]),
                  pack_bf16(acc1[4 * j + 4], acc1[4 * j + 5]), pack_bf16(acc1[4 * j + 6], acc1[4 * j + 7]));
    }
  }
  fence_async_smem();
  wg_bar(1);
  TSTAMP(56);
#pragma unroll 1
  for (int it = 0; it < 8; it += 2) {
    float pA[16], pB[16], nA[20], nB[20];
    uint32_t posA[8], negA[8], posB[8], negB[8];
    q_issue_pq(pA, sbase, it);
    q_issue_pq(pB, sbase, it + 1);
    wgmma_wait<1>();
    fence_regs(pA);
    dual_softmax(pA, posA, negA);
    mbar_wait(sbase + OFF_BAR + B_KVX + 8 * (it >> 2), 0);
    if (it == 0) TSTAMP(57);
    if (it == 4) TSTAMP(58);
    q_issue_num(nA, posA, negA, sbase, it);
    wgmma_wait<1>();
    fence_regs(pB);
    dual_softmax(pB, posB, negB);
    q_issue_num(nB, posB, negB, sbase, it + 1);
    wgmma_wait<1>();
    fence_regs(nA);
    q_store_o(nA, sbase, it);
    wgmma_wait<0>();
    fence_regs(nB);
    q_store_o(nB, sbase, it + 1);
  }
  TSTAMP(60);
  fence_async_smem();
  wg_bar(1);
  if (t == 0) {
    tma_store_2d(&prm.tmO, sbase + OFF_PHI, 64 * g, 128 * rb_idx);
    tma_store_2d(&prm.tmO, sbase + OFF_PHI + 16384, 64 * (g + 8), 128 * rb_idx);
    bulk_commit();
    bulk_wait_all();
    red_relaxed_add(&g_flags.ocnt[rb_idx * 8], 1);
  }
}

__device__ __forceinline__ void helper_kv(uint32_t sbase, int g, unsigned epoch) {
  const int h = threadIdx.x - 32;
  mbar_wait(sbase + OFF_BAR + B_E3, 0);
#pragma unroll 1
  for (int pr = 0; pr < 2; pr++) {
    if ((h & 31) == 0) wait_ge(&g_flags.kvcnt[(g + 8 * pr) * 8], 16u * epoch);
    __syncwarp();
    const float4* src = reinterpret_cast<const float4*>(g_kv + (size_t)(2 * g + 16 * pr) * 64 * KVW);
#pragma unroll 1
    for (int ib = 0; ib < 2; ib++) {
      float4 u[7];
#pragma unroll
      for (int i = 0; i < 7; i++) u[i] = __ldcg(src + min((ib * 7 + i) * 96 + h, 1279));
#pragma unroll
      for (int i = 0; i < 7; i++) {
        const int idx = min((ib * 7 + i) * 96 + h, 1279);
        const int f2 = idx / 10, j = idx - f2 * 10;
        const uint32_t dst = sbase + OFF_V + pr * 10240 + (f2 >> 3) * 640 + (j >> 1) * 128 + (f2 & 7) * 16 + (j & 1) * 8;
        asm volatile("st.shared.v2.b32 [%0], {%1, %2};" ::"r"(dst), "r"(pack_bf16(u[i].x, u[i].y)), "r"(pack_bf16(u[i].z, u[i].w)) : "memory");
      }
    }
    fence_async_smem();
    __syncwarp();
    if ((h & 31) == 0) mbar_arrive(sbase + OFF_BAR + B_KVX + 8 * pr);
  }
}

__device__ __forceinline__ float bf16_round(float x) { return __bfloat162float(__float2bfloat16(x)); }
__device__ __forceinline__ void store_out(const float (&a)[64], float* dst) {
#pragma unroll
  for (int j = 0; j < 16; j++) {
    __stcs(reinterpret_cast<float2*>(dst + 8 * j), make_float2(bf16_round(a[4 * j]), bf16_round(a[4 * j + 1])));
    __stcs(reinterpret_cast<float2*>(dst + 8 * 2048 + 8 * j), make_float2(bf16_round(a[4 * j + 2]), bf16_round(a[4 * j + 3])));
  }
}
__device__ __forceinline__ void store_y(const float (&a)[64], const Params& prm, int rb, int g, int m0, int q) {
  const __nv_bfloat162* dk = reinterpret_cast<const __nv_bfloat162*>(prm.dskip + 128 * g + 2 * q);
#pragma unroll
  for (int h = 0; h < 2; h++) {
    const int m = m0 + 8 * h;
    const int tt = rb * 128 + 32 * ((m >> 3) & 3) + 8 * (m >> 5) + (m & 7);
    const __nv_bfloat162* xr = reinterpret_cast<const __nv_bfloat162*>(prm.xB + (size_t)tt * DM + 128 * g + 2 * q);
    float* dst = prm.out + (size_t)tt * 2048 + 1024 + 128 * g + 2 * q;
#pragma unroll
    for (int j = 0; j < 16; j++) {
      const float2 sk = __bfloat1622float2(__hmul2(__ldg(xr + 4 * j), __ldg(dk + 4 * j)));
      __stcs(reinterpret_cast<float2*>(dst + 8 * j), make_float2(a[4 * j + 2 * h] + sk.x, a[4 * j + 2 * h + 1] + sk.y));
    }
  }
}

__global__ void __launch_bounds__(384, 1) fused_kernel(const __grid_constant__ Params prm) {
  extern __shared__ uint8_t smem_raw[];
  const uint32_t sbase = (smem_u32(smem_raw) + 1023) & ~1023u;
  const uint32_t bars = sbase + OFF_BAR;
  const int tid = threadIdx.x, wg = __shfl_sync(0xffffffffu, tid >> 7, 0);
  const int cl = blockIdx.x >> 1, rank = blockIdx.x & 1;
  const int g = cl >> 3, rb = 2 * (cl & 7) + rank;

  if (tid == 0) {
    for (int s = 0; s < STAGES; s++) { mbar_init(bars + 8 * s, 1);
      mbar_init(bars + B_EMPTY + 8 * s, 8);
    }
    mbar_init(bars + B_ORD, 1); mbar_init(bars + B_ORD + 8, 1); mbar_init(bars + B_EBF, 1); mbar_init(bars + B_WPHI, 1); mbar_init(bars + B_EPOCH, 1); mbar_init(bars + B_KVX, 3); mbar_init(bars + B_KVX + 8, 3); mbar_init(bars + B_E3, 1);
    asm volatile("fence.mbarrier_init.release.cluster;" ::: "memory");
  } else if (tid == 32) {
    prefetch_tm(&prm.tmXB); prefetch_tm(rank ? &prm.tmBim : &prm.tmBre); prefetch_tm(&prm.tmWphi);
    prefetch_tm(&prm.tmXA); prefetch_tm(&prm.tmWqkv); prefetch_tm(&prm.tmHT);
    prefetch_tm(&prm.tmCre); prefetch_tm(&prm.tmCim); prefetch_tm(&prm.tmO); prefetch_tm(&prm.tmWo);
  } else if (tid >= 64 && tid < 128) {
    asm volatile("st.shared.v4.b32 [%0], {%1, %2, %2, %2};" ::"r"(sbase + OFF_ONES + (tid - 64) * 16), "r"(0x00003F80u), "r"(0u) : "memory");
    fence_async_smem();
  }
  __syncthreads();
  asm volatile("barrier.cluster.arrive.relaxed.aligned;\nbarrier.cluster.wait.acquire.aligned;" ::: "memory");

  if (wg == 0) {
    reg_dealloc<56>();
    const int warp = tid >> 5, lane = tid & 31;
    if (warp == 0) {
      if (lane == 0) {
        TSTAMP(0);
        mbar_expect_tx(bars + B_WPHI, 8192);
        tma_2d(sbase + OFF_WPHI, &prm.tmWphi, 0, 64 * g, bars + B_WPHI);
        tma_2d(sbase + OFF_WPHI + 4096, &prm.tmWphi, 0, 64 * g + 512, bars + B_WPHI);
        int stage = 0;
        uint32_t phase = 1;
        unsigned epoch = 0;
        for (int tile = 0; tile < 7; tile++) {
          const int nkb = (tile == 5) ? 32 : 16;
          if (tile == 5) {
            mbar_wait(bars + B_EPOCH, 0);
            asm volatile("ld.shared.u32 %0, [%1];" : "=r"(epoch) : "r"(bars + B_EPOCHV) : "memory");
            wait_ge(&g_flags.hcnt[rb * 8], 16u * epoch);
          } else if (tile == 6) {
            wait_ge(&g_flags.ocnt[rb * 8], 8u * epoch);
          }
          for (int kb = 0; kb < nkb; kb++) {
            mbar_wait(bars + B_EMPTY + 8 * stage, phase);
            const uint32_t full = bars + 8 * stage;
            const uint32_t sw = sbase + stage * STAGE_BYTES, sx = sw + 16384, swr = sw + rank * 8192;
            mbar_expect_tx(full, STAGE_BYTES);
            if (tile < 2) {
              tma_2d_mc(swr, rank ? &prm.tmBim : &prm.tmBre, kb * 64, 64 * (g + 8 * tile), full);
              tma_5d(sx, &prm.tmXB, kb * 64, 0, 0, 0, rb, full);
            } else if (tile < 4) {
              tma_2d_mc(swr, &prm.tmWqkv, 1024 + rank * 1024 + 64 * (g + 8 * (tile - 2)), kb * 64, full);
              tma_2d(sx, &prm.tmXA, kb * 64, rb * 128, full);
            } else if (tile == 4) {
              tma_2d_mc(swr, &prm.tmWqkv, 64 * (g + 8 * rank), kb * 64, full);
              tma_2d(sx, &prm.tmXA, kb * 64, rb * 128, full);
            } else if (tile == 5) {
              tma_2d_mc(swr, kb < 16 ? &prm.tmCre : &prm.tmCim, (kb & 15) * 64, 128 * g + 64 * rank, full);
              tma_3d(sx, &prm.tmHT, 0, kb * 64, 2 * rb, full);
            } else {
              tma_2d_mc(swr, &prm.tmWo, 128 * g + 64 * rank, kb * 64, full);
              tma_2d(sx, &prm.tmO, kb * 64, rb * 128, full);
            }
            if (++stage == STAGES) { stage = 0; phase ^= 1; }
          }
        }
        TSTAMP(1);
      }
    } else {
      unsigned epoch = 0;
      if (warp == 1) {
      if (lane == 0) {
        epoch = (atomicAdd(&g_flags.ticket, 1u) >> 7) + 1u;
        asm volatile("st.shared.u32 [%0], %1;" ::"r"(bars + B_EPOCHV), "r"(epoch) : "memory");
        mbar_arrive(bars + B_EPOCH);
      }
      uint4* z = reinterpret_cast<uint4*>(g_kv) + blockIdx.x * 160;
#pragma unroll
      for (int i = 0; i < 5; i++) __stcg(z + i * 32 + lane, make_uint4(0, 0, 0, 0));
      __syncwarp();
      if (lane == 0) red_release_add(&g_flags.zero_cnt, 1);
      }
      mbar_wait(bars + B_EPOCH, 0);
      asm volatile("ld.shared.u32 %0, [%1];" : "=r"(epoch) : "r"(bars + B_EPOCHV) : "memory");
      helper_kv(sbase, g, epoch);
    }
    __syncwarp();
    asm volatile("barrier.cluster.arrive.relaxed.aligned;\nbarrier.cluster.wait.aligned;" ::: "memory");
  } else {
    reg_alloc<224>();
    const int cw = wg - 1;
    const int t = tid & 127, lane = t & 31, w = t >> 5, q = lane & 3, r8 = lane >> 2;
    float acc0[64], acc1[64];
    unsigned epoch;
    {
      const int G = g + 8 * cw;
      ChanParams cp[2];
      cp[0] = chan_params(prm, 64 * G + 16 * w + r8);
      cp[1] = chan_params(prm, 64 * G + 16 * w + r8 + 8);
      TSTAMP(2 + 12 * cw);
      mainloop<0>(acc0, acc1, 16 * cw, 16, sbase, cw, cw ^ 1);
      TSTAMP(3 + 12 * cw);
      mbar_wait(bars + B_EPOCH, 0);
      asm volatile("ld.shared.u32 %0, [%1];" : "=r"(epoch) : "r"(bars + B_EPOCHV) : "memory");
      epi_bu(acc0, acc1, cp, prm, sbase, G, rb, cw, epoch);
      TSTAMP(4 + 12 * cw);
    }
    {
      mainloop<1>(acc0, acc1, 32 + 16 * cw, 16, sbase, cw, cw);
      TSTAMP(5 + 12 * cw);
      mbar_wait(bars + B_WPHI, 0);
      mbar_wait(bars + B_EBF, cw ^ 1);
      epi_kv(acc0, acc1, sbase, g + 8 * cw, 2 * cw, cw, epoch);
      TSTAMP(6 + 12 * cw);
    }
    if (cw == 0) {
      mainloop<1>(acc0, acc1, 64, 16, sbase, 0, 1);
      TSTAMP(7);
      mbar_wait(bars + B_EBF, 1);
      epi_q(acc0, acc1, prm, sbase, g, rb);
      TSTAMP(8);
      mainloop<1>(acc0, acc1, 112, 16, sbase, 0, 0);
      TSTAMP(9);
      float* dst = prm.out + (size_t)(rb * 128 + 16 * w + r8) * 2048 + 128 * g + 2 * q;
      store_out(acc0, dst);
      store_out(acc1, dst + (size_t)64 * 2048);
      TSTAMP(10);
    } else {
      mainloop<2>(acc0, acc1, 80, 32, sbase, 1, 0);
      TSTAMP(19);
      store_y(acc0, prm, rb, g, 16 * w + r8, q);
      store_y(acc1, prm, rb, g, 16 * w + r8 + 64, q);
      TSTAMP(20);
    }
    asm volatile("barrier.cluster.arrive.relaxed.aligned;\nbarrier.cluster.wait.aligned;" ::: "memory");
  }
}

typedef CUresult (*PFN_encodeTiled)(CUtensorMap*, CUtensorMapDataType, cuuint32_t, void*, const cuuint64_t*, const cuuint64_t*,
                                    const cuuint32_t*, const cuuint32_t*, CUtensorMapInterleave, CUtensorMapSwizzle,
                                    CUtensorMapL2promotion, CUtensorMapFloatOOBfill);

bool make_tm(PFN_encodeTiled enc, CUtensorMap* tm, const void* base, int rank, const uint64_t* dims, const uint64_t* strides,
             const uint32_t* box, CUtensorMapSwizzle sw) {
  cuuint64_t gd[5], gs[5];
  cuuint32_t bx[5], es[5];
  for (int i = 0; i < rank; i++) { gd[i] = dims[i]; bx[i] = box[i]; es[i] = 1; }
  for (int i = 0; i + 1 < rank; i++) gs[i] = strides[i];
  return enc(tm, CU_TENSOR_MAP_DATA_TYPE_BFLOAT16, rank, const_cast<void*>(base), gd, gs, bx, es, CU_TENSOR_MAP_INTERLEAVE_NONE, sw,
             CU_TENSOR_MAP_L2_PROMOTION_L2_256B, CU_TENSOR_MAP_FLOAT_OOB_FILL_NONE) == CUDA_SUCCESS;
}
bool make_tm2(PFN_encodeTiled enc, CUtensorMap* tm, const void* base, uint64_t inner, uint64_t outer, uint32_t b0, uint32_t b1,
              CUtensorMapSwizzle sw = CU_TENSOR_MAP_SWIZZLE_128B) {
  const uint64_t dims[2] = {inner, outer}, str[1] = {inner * 2};
  const uint32_t box[2] = {b0, b1};
  return make_tm(enc, tm, base, 2, dims, str, box, sw);
}

}

extern "C" void kernel_launch(void* const* d_in, const int* in_sizes, int n_in, void* d_out, int out_size) {
  (void)in_sizes; (void)n_in; (void)out_size;
  static PFN_encodeTiled enc = nullptr;
  static void *pHT = nullptr, *pO = nullptr;
  if (!enc) {
    void* fn = nullptr;
    cudaDriverEntryPointQueryResult qr;
    if (cudaGetDriverEntryPoint("cuTensorMapEncodeTiled", &fn, cudaEnableDefault, &qr) != cudaSuccess || !fn) return;
    enc = (PFN_encodeTiled)fn;
    cudaFuncSetAttribute(fused_kernel, cudaFuncAttributeMaxDynamicSharedMemorySize, SMEM_BYTES);
    cudaGetSymbolAddress(&pHT, g_HT);
    cudaGetSymbolAddress(&pO, g_O);
  }
  Params prm;
  bool ok = true;
  {
    const uint64_t dims[5] = {1024, 2, 4, 16, 16}, str[4] = {2048, 65536, 4096, 262144};
    const uint32_t box[5] = {64, 2, 4, 16, 1};
    ok &= make_tm(enc, &prm.tmXB, d_in[4], 5, dims, str, box, CU_TENSOR_MAP_SWIZZLE_128B);
  }
  ok &= make_tm2(enc, &prm.tmBre, d_in[7], 1024, 1024, 64, 64);
  ok &= make_tm2(enc, &prm.tmBim, d_in[8], 1024, 1024, 64, 64);
  ok &= make_tm2(enc, &prm.tmXA, d_in[0], 1024, 2048, 64, 128);
  ok &= make_tm2(enc, &prm.tmWqkv, d_in[1], 3072, 1024, 64, 64);
  ok &= make_tm2(enc, &prm.tmWphi, d_in[2], 32, 1024, 32, 64, CU_TENSOR_MAP_SWIZZLE_64B);
  {
    const uint64_t dims[3] = {64, 2048, 32}, str[2] = {4096, 128};
    const uint32_t box[3] = {64, 64, 2};
    ok &= make_tm(enc, &prm.tmHT, pHT, 3, dims, str, box, CU_TENSOR_MAP_SWIZZLE_128B);
  }
  ok &= make_tm2(enc, &prm.tmCre, d_in[9], 1024, 1024, 64, 64);
  ok &= make_tm2(enc, &prm.tmCim, d_in[10], 1024, 1024, 64, 64);
  ok &= make_tm2(enc, &prm.tmO, pO, 1024, 2048, 64, 128);
  ok &= make_tm2(enc, &prm.tmWo, d_in[3], 1024, 1024, 64, 64);
  if (!ok) return;
  prm.xB = (const __nv_bfloat16*)d_in[4];
  prm.lam_re = (const __nv_bfloat16*)d_in[5];
  prm.lam_im = (const __nv_bfloat16*)d_in[6];
  prm.log_dt = (const __nv_bfloat16*)d_in[11];
  prm.dskip = (const __nv_bfloat16*)d_in[12];
  prm.out = (float*)d_out;

  cudaLaunchConfig_t cfg = {};
  cfg.gridDim = dim3(128);
  cfg.blockDim = dim3(384);
  cfg.dynamicSmemBytes = SMEM_BYTES;
  cfg.stream = cudaStreamPerThread;
  cudaLaunchAttribute attr[1];
  attr[0].id = cudaLaunchAttributeClusterDimension;
  attr[0].val.clusterDim.x = 2; attr[0].val.clusterDim.y = 1; attr[0].val.clusterDim.z = 1;
  cfg.attrs = attr;
  cfg.numAttrs = 1;
  cudaLaunchKernelEx(&cfg, fused_kernel, prm);
}
```

```cpp
#include <cuda_runtime.h>
#include <cuda_bf16.h>
#include <cuda.h>
#include <stdint.h>

namespace {

constexpr int SEQ = 2048;
constexpr int DM = 1024;
#define NSTAGES 5
constexpr int STAGES = NSTAGES;
constexpr int STAGE_BYTES = 32768;
constexpr int OFF_EB = 5 * STAGE_BYTES;
constexpr int OFF_PHI = OFF_EB;
constexpr int OFF_V = OFF_EB + 32768;
constexpr int OFF_WPHI = OFF_EB + 53248;
constexpr int OFF_ONES = OFF_EB + 61440;
constexpr int OFF_BAR = OFF_EB + 62464;
constexpr int SMEM_BYTES = OFF_BAR + 256 + 1024;
constexpr int B_EMPTY = 64, B_ORD = 128, B_EBF = 144, B_WPHI = 152, B_EPOCH = 160, B_KVX = 168  , B_E3 = 184, B_EPOCHV = 192;

constexpr int KVW = 40;

struct Params {
  CUtensorMap tmXB;
  CUtensorMap tmBre, tmBim;
  CUtensorMap tmXA;
  CUtensorMap tmWqkv;
  CUtensorMap tmWphi;
  CUtensorMap tmHT;
  CUtensorMap tmCre, tmCim;
  CUtensorMap tmO;
  CUtensorMap tmWo;
  const __nv_bfloat16* xB;
  const __nv_bfloat16* lam_re;
  const __nv_bfloat16* lam_im;
  const __nv_bfloat16* log_dt;
  const __nv_bfloat16* dskip;
  float* out;
};

__device__ __nv_bfloat16 g_HT[2048 * 2048];
__device__ __nv_bfloat16 g_O[SEQ * DM];
__device__ float g_kv[32 * 64 * KVW];
__device__ uint4 g_E[16 * 16 * 64];
struct Flags {
  unsigned ticket;   unsigned pad0[31];
  unsigned zero_cnt; unsigned pad1[31];
  unsigned hcnt[16 * 8];
  unsigned kvcnt[16 * 8];
  unsigned ocnt[16 * 8];
};
__device__ Flags g_flags;
#define TSTAMP(i)
#define QT(i)

__device__ unsigned g_abort;
__device__ __forceinline__ bool give_up(unsigned spins, unsigned limit) {
  if ((spins & 255u) != 0) return false;
  if (*(volatile unsigned*)&g_abort) return true;
  if (spins > limit) { *(volatile unsigned*)&g_abort = 1u; return true; }
  return false;
}
__device__ __forceinline__ uint32_t smem_u32(const void* p) { return (uint32_t)__cvta_generic_to_shared(p); }
__device__ __forceinline__ void mbar_init(uint32_t bar, uint32_t count) {
  asm volatile("mbarrier.init.shared::cta.b64 [%0], %1;" ::"r"(bar), "r"(count));
}
__device__ __forceinline__ void mbar_expect_tx(uint32_t bar, uint32_t bytes) {
  asm volatile("mbarrier.arrive.expect_tx.shared::cta.b64 _, [%0], %1;" ::"r"(bar), "r"(bytes) : "memory");
}
__device__ __forceinline__ void mbar_arrive(uint32_t bar) {
  asm volatile("mbarrier.arrive.shared::cta.b64 _, [%0];" ::"r"(bar) : "memory");
}
__device__ __forceinline__ void mbar_arrive_cluster(uint32_t bar, uint32_t cta) {
  asm volatile("{\n.reg .b32 ra;\nmapa.shared::cluster.u32 ra, %0, %1;\nmbarrier.arrive.shared::cluster.b64 _, [ra];\n}" ::"r"(bar), "r"(cta) : "memory");
}
__device__ __forceinline__ bool mbar_try(uint32_t bar, uint32_t parity) {
  uint32_t ok;
  asm volatile("{\n.reg .pred p;\nmbarrier.try_wait.parity.shared::cta.b64 p, [%1], %2;\nselp.u32 %0, 1, 0, p;\n}" : "=r"(ok) : "r"(bar), "r"(parity) : "memory");
  return ok != 0;
}
__device__ __forceinline__ void mbar_wait(uint32_t bar, uint32_t parity) {
  if (mbar_try(bar, parity)) return;
  uint32_t spins = 0;
  while (!mbar_try(bar, parity)) {
    if (give_up(++spins, 1u << 21)) break;
  }
}
__device__ __forceinline__ void mbar_wait_sleep(uint32_t bar, uint32_t parity) {
  uint32_t spins = 0;
  while (!mbar_try(bar, parity)) {
    __nanosleep(500);
    if (give_up(++spins, 1u << 20)) break;
  }
}
__device__ __forceinline__ unsigned ld_relaxed(const unsigned* p) {
  unsigned v;
  asm volatile("ld.relaxed.gpu.global.u32 %0, [%1];" : "=r"(v) : "l"(p) : "memory");
  return v;
}
__device__ __forceinline__ void wait_ge(const unsigned* p, unsigned target) {
  unsigned spins = 0;
  while ((int)(ld_relaxed(p) - target) < 0) {
    __nanosleep(128);
    if (give_up(++spins, 1u << 20)) break;
  }
}
__device__ __forceinline__ void red_release_add(unsigned* p, unsigned v) {
  asm volatile("red.release.gpu.global.add.u32 [%0], %1;" ::"l"(p), "r"(v) : "memory");
}
__device__ __forceinline__ void red_relaxed_add(unsigned* p, unsigned v) {
  asm volatile("red.relaxed.gpu.global.add.u32 [%0], %1;" ::"l"(p), "r"(v) : "memory");
}
__device__ __forceinline__ void st_tagged(uint4* p, float a, float b, unsigned tag) {
  const unsigned long long w0 = ((unsigned long long)tag << 32) | __float_as_uint(a);
  const unsigned long long w1 = ((unsigned long long)tag << 32) | __float_as_uint(b);
  asm volatile("st.relaxed.gpu.global.v2.b64 [%0], {%1, %2};" ::"l"(p), "l"(w0), "l"(w1) : "memory");
}
__device__ __forceinline__ bool ld_tagged(const uint4* p, float& a, float& b, unsigned tag) {
  unsigned long long w0, w1;
  asm volatile("ld.relaxed.gpu.global.v2.b64 {%0, %1}, [%2];" : "=l"(w0), "=l"(w1) : "l"(p) : "memory");
  a = __uint_as_float((unsigned)w0);
  b = __uint_as_float((unsigned)w1);
  return (unsigned)(w0 >> 32) == tag && (unsigned)(w1 >> 32) == tag;
}
__device__ __forceinline__ void bulk_commit() { asm volatile("cp.async.bulk.commit_group;" ::: "memory"); }
__device__ __forceinline__ void bulk_wait_all() { asm volatile("cp.async.bulk.wait_group 0;" ::: "memory"); }
__device__ __forceinline__ void bulk_reduce_f32(float* dst, uint32_t src, uint32_t bytes) {
  asm volatile("cp.reduce.async.bulk.global.shared::cta.bulk_group.add.f32 [%0], [%1], %2;" ::"l"(dst), "r"(src), "r"(bytes) : "memory");
}
__device__ __forceinline__ void tma_store_3d(const CUtensorMap* tm, uint32_t src, int c0, int c1, int c2) {
  asm volatile("cp.async.bulk.tensor.3d.global.shared::cta.bulk_group [%0, {%2, %3, %4}], [%1];"
               ::"l"(tm), "r"(src), "r"(c0), "r"(c1), "r"(c2) : "memory");
}
__device__ __forceinline__ void fence_gpu() { asm volatile("fence.acq_rel.gpu;" ::: "memory"); }
__device__ __forceinline__ void fence_async_all() { asm volatile("fence.proxy.async;" ::: "memory"); }
__device__ __forceinline__ void fence_async_smem() { asm volatile("fence.proxy.async.shared::cta;" ::: "memory"); }
__device__ __forceinline__ void red_add_v2(float* p, float a, float b) {
  asm volatile("red.global.add.v2.f32 [%0], {%1, %2};" ::"l"(p), "f"(a), "f"(b) : "memory");
}
__device__ __forceinline__ void tma_2d(uint32_t dst, const CUtensorMap* tm, int c0, int c1, uint32_t bar) {
  asm volatile("cp.async.bulk.tensor.2d.shared::cluster.global.mbarrier::complete_tx::bytes [%0], [%1, {%3, %4}], [%2];"
               ::"r"(dst), "l"(tm), "r"(bar), "r"(c0), "r"(c1) : "memory");
}
__device__ __forceinline__ void tma_3d(uint32_t dst, const CUtensorMap* tm, int c0, int c1, int c2, uint32_t bar) {
  asm volatile("cp.async.bulk.tensor.3d.shared::cluster.global.mbarrier::complete_tx::bytes [%0], [%1, {%3, %4, %5}], [%2];"
               ::"r"(dst), "l"(tm), "r"(bar), "r"(c0), "r"(c1), "r"(c2) : "memory");
}
__device__ __forceinline__ void tma_5d(uint32_t dst, const CUtensorMap* tm, int c0, int c1, int c2, int c3, int c4, uint32_t bar) {
  asm volatile("cp.async.bulk.tensor.5d.shared::cluster.global.mbarrier::complete_tx::bytes [%0], [%1, {%3, %4, %5, %6, %7}], [%2];"
               ::"r"(dst), "l"(tm), "r"(bar), "r"(c0), "r"(c1), "r"(c2), "r"(c3), "r"(c4) : "memory");
}
__device__ __forceinline__ void tma_2d_mc(uint32_t dst, const CUtensorMap* tm, int c0, int c1, uint32_t bar) {
  asm volatile("cp.async.bulk.tensor.2d.shared::cluster.global.mbarrier::complete_tx::bytes.multicast::cluster [%0], [%1, {%3, %4}], [%2], %5;"
               ::"r"(dst), "l"(tm), "r"(bar), "r"(c0), "r"(c1), "h"((uint16_t)3) : "memory");
}
__device__ __forceinline__ void tma_store_2d(const CUtensorMap* tm, uint32_t src, int c0, int c1) {
  asm volatile("cp.async.bulk.tensor.2d.global.shared::cta.bulk_group [%0, {%2, %3}], [%1];"
               ::"l"(tm), "r"(src), "r"(c0), "r"(c1) : "memory");
}
__device__ __forceinline__ void prefetch_tm(const CUtensorMap* tm) {
  asm volatile("prefetch.tensormap [%0];" ::"l"(tm) : "memory");
}
__device__ __forceinline__ void wgmma_fence() { asm volatile("wgmma.fence.sync.aligned;" ::: "memory"); }
__device__ __forceinline__ void wgmma_commit() { asm volatile("wgmma.commit_group.sync.aligned;" ::: "memory"); }
template <int N> __device__ __forceinline__ void wgmma_wait() { asm volatile("wgmma.wait_group.sync.aligned %0;" ::"n"(N) : "memory"); }
__device__ __forceinline__ void wg_bar(int id) {
  if (id == 1) asm volatile("bar.sync 1, 128;" ::: "memory");
  else asm volatile("bar.sync 2, 128;" ::: "memory");
}
template <int R> __device__ __forceinline__ void reg_alloc() { asm volatile("setmaxnreg.inc.sync.aligned.u32 %0;" ::"n"(R)); }
template <int R> __device__ __forceinline__ void reg_dealloc() { asm volatile("setmaxnreg.dec.sync.aligned.u32 %0;" ::"n"(R)); }

__device__ __forceinline__ uint64_t make_desc(uint32_t saddr, uint32_t lbo_bytes, uint32_t sbo_bytes, uint32_t layout) {
  uint64_t d = (uint64_t)((saddr & 0x3FFFF) >> 4);
  d |= (uint64_t)((lbo_bytes & 0x3FFFF) >> 4) << 16;
  d |= (uint64_t)((sbo_bytes & 0x3FFFF) >> 4) << 32;
  d |= (uint64_t)layout << 62;
  return d;
}
__device__ __forceinline__ uint64_t desc128(uint32_t lo) { return ((uint64_t)0x40000040u << 32) | lo; }
__device__ __forceinline__ uint32_t pack_bf16(float lo, float hi) {
  uint32_t r;
  asm("cvt.rn.bf16x2.f32 %0, %1, %2;" : "=r"(r) : "f"(hi), "f"(lo));
  return r;
}
__device__ __forceinline__ float ex2(float x) { float y; asm("ex2.approx.ftz.f32 %0, %1;" : "=f"(y) : "f"(x)); return y; }
__device__ __forceinline__ float rcp(float x) { float y; asm("rcp.approx.ftz.f32 %0, %1;" : "=f"(y) : "f"(x)); return y; }
__device__ __forceinline__ void stmatrix_x4(uint32_t addr, uint32_t r0, uint32_t r1, uint32_t r2, uint32_t r3) {
  asm volatile("stmatrix.sync.aligned.m8n8.x4.shared.b16 [%0], {%1, %2, %3, %4};" ::"r"(addr), "r"(r0), "r"(r1), "r"(r2), "r"(r3) : "memory");
}
template <int N> __device__ __forceinline__ void fence_regs(float (&d)[N]) {
#pragma unroll
  for (int i = 0; i < N; i++) asm volatile("" : "+f"(d[i])::"memory");
}

template <int TA, int TB>
__device__ __forceinline__ void wgmma_m64n128k16_ss(float (&d)[64], uint64_t descA, uint64_t descB, int scaleD) {
  asm volatile("{\n.reg .pred p;\nsetp.ne.b32 p, %66, 0;\n"
    "wgmma.mma_async.sync.aligned.m64n128k16.f32.bf16.bf16 "
    "{%0, %1, %2, %3, %4, %5, %6, %7, %8, %9, %10, %11, %12, %13, %14, %15, %16, %17, %18, %19, %20, %21, %22, %23, %24, %25, %26, %27, %28, %29, %30, %31, %32, %33, %34, %35, %36, %37, %38, %39, %40, %41, %42, %43, %44, %45, %46, %47, %48, %49, %50, %51, %52, %53, %54, %55, %56, %57, %58, %59, %60, %61, %62, %63}, "
    "%64, %65, p, 1, 1, %67, %68;\n}\n"
    : "+f"(d[0]), "+f"(d[1]), "+f"(d[2]), "+f"(d[3]), "+f"(d[4]), "+f"(d[5]), "+f"(d[6]), "+f"(d[7]), "+f"(d[8]), "+f"(d[9]), "+f"(d[10]), "+f"(d[11]), "+f"(d[12]), "+f"(d[13]), "+f"(d[14]), "+f"(d[15]), "+f"(d[16]), "+f"(d[17]), "+f"(d[18]), "+f"(d[19]), "+f"(d[20]), "+f"(d[21]), "+f"(d[22]), "+f"(d[23]), "+f"(d[24]), "+f"(d[25]), "+f"(d[26]), "+f"(d[27]), "+f"(d[28]), "+f"(d[29]), "+f"(d[30]), "+f"(d[31]), "+f"(d[32]), "+f"(d[33]), "+f"(d[34]), "+f"(d[35]), "+f"(d[36]), "+f"(d[37]), "+f"(d[38]), "+f"(d[39]), "+f"(d[40]), "+f"(d[41]), "+f"(d[42]), "+f"(d[43]), "+f"(d[44]), "+f"(d[45]), "+f"(d[46]), "+f"(d[47]), "+f"(d[48]), "+f"(d[49]), "+f"(d[50]), "+f"(d[51]), "+f"(d[52]), "+f"(d[53]), "+f"(d[54]), "+f"(d[55]), "+f"(d[56]), "+f"(d[57]), "+f"(d[58]), "+f"(d[59]), "+f"(d[60]), "+f"(d[61]), "+f"(d[62]), "+f"(d[63])
    : "l"(descA), "l"(descB), "r"(scaleD), "n"(TA), "n"(TB));
}

template <int TB>
__device__ __forceinline__ void wgmma_m64n32k16_rs(float (&d)[16], uint32_t a0, uint32_t a1, uint32_t a2, uint32_t a3, uint64_t descB, int scaleD) {
  asm volatile("{\n.reg .pred p;\nsetp.ne.b32 p, %21, 0;\n"
    "wgmma.mma_async.sync.aligned.m64n32k16.f32.bf16.bf16 "
    "{%0, %1, %2, %3, %4, %5, %6, %7, %8, %9, %10, %11, %12, %13, %14, %15}, "
    "{%16, %17, %18, %19}, %20, p, 1, 1, %22;\n}\n"
    : "+f"(d[0]), "+f"(d[1]), "+f"(d[2]), "+f"(d[3]), "+f"(d[4]), "+f"(d[5]), "+f"(d[6]), "+f"(d[7]), "+f"(d[8]), "+f"(d[9]), "+f"(d[10]), "+f"(d[11]), "+f"(d[12]), "+f"(d[13]), "+f"(d[14]), "+f"(d[15])
    : "r"(a0), "r"(a1), "r"(a2), "r"(a3), "l"(descB), "r"(scaleD), "n"(TB));
}

template <int TB>
__device__ __forceinline__ void wgmma_m64n40k16_rs(float (&d)[20], uint32_t a0, uint32_t a1, uint32_t a2, uint32_t a3, uint64_t descB, int scaleD) {
  asm volatile("{\n.reg .pred p;\nsetp.ne.b32 p, %25, 0;\n"
    "wgmma.mma_async.sync.aligned.m64n40k16.f32.bf16.bf16 "
    "{%0, %1, %2, %3, %4, %5, %6, %7, %8, %9, %10, %11, %12, %13, %14, %15, %16, %17, %18, %19}, "
    "{%20, %21, %22, %23}, %24, p, 1, 1, %26;\n}\n"
    : "+f"(d[0]), "+f"(d[1]), "+f"(d[2]), "+f"(d[3]), "+f"(d[4]), "+f"(d[5]), "+f"(d[6]), "+f"(d[7]), "+f"(d[8]), "+f"(d[9]), "+f"(d[10]), "+f"(d[11]), "+f"(d[12]), "+f"(d[13]), "+f"(d[14]), "+f"(d[15]), "+f"(d[16]), "+f"(d[17]), "+f"(d[18]), "+f"(d[19])
    : "r"(a0), "r"(a1), "r"(a2), "r"(a3), "l"(descB), "r"(scaleD), "n"(TB));
}

template <int TA, int TB>
__device__ __forceinline__ void wgmma_m64n40k16_ss(float (&d)[20], uint64_t descA, uint64_t descB, int scaleD) {
  asm volatile("{\n.reg .pred p;\nsetp.ne.b32 p, %22, 0;\n"
    "wgmma.mma_async.sync.aligned.m64n40k16.f32.bf16.bf16 "
    "{%0, %1, %2, %3, %4, %5, %6, %7, %8, %9, %10, %11, %12, %13, %14, %15, %16, %17, %18, %19}, "
    "%20, %21, p, 1, 1, %23, %24;\n}\n"
    : "+f"(d[0]), "+f"(d[1]), "+f"(d[2]), "+f"(d[3]), "+f"(d[4]), "+f"(d[5]), "+f"(d[6]), "+f"(d[7]), "+f"(d[8]), "+f"(d[9]), "+f"(d[10]), "+f"(d[11]), "+f"(d[12]), "+f"(d[13]), "+f"(d[14]), "+f"(d[15]), "+f"(d[16]), "+f"(d[17]), "+f"(d[18]), "+f"(d[19])
    : "l"(descA), "l"(descB), "r"(scaleD), "n"(TA), "n"(TB));
}

template <int TA, int TB>
__device__ __forceinline__ void wgmma_m64n32k16_ss(float (&d)[16], uint64_t descA, uint64_t descB, int scaleD) {
  asm volatile("{\n.reg .pred p;\nsetp.ne.b32 p, %18, 0;\n"
    "wgmma.mma_async.sync.aligned.m64n32k16.f32.bf16.bf16 "
    "{%0, %1, %2, %3, %4, %5, %6, %7, %8, %9, %10, %11, %12, %13, %14, %15}, "
    "%16, %17, p, 1, 1, %19, %20;\n}\n"
    : "+f"(d[0]), "+f"(d[1]), "+f"(d[2]), "+f"(d[3]), "+f"(d[4]), "+f"(d[5]), "+f"(d[6]), "+f"(d[7]), "+f"(d[8]), "+f"(d[9]), "+f"(d[10]), "+f"(d[11]), "+f"(d[12]), "+f"(d[13]), "+f"(d[14]), "+f"(d[15])
    : "l"(descA), "l"(descB), "r"(scaleD), "n"(TA), "n"(TB));
}

template <int MODE>
__device__ __forceinline__ void mainloop(float (&acc0)[64], float (&acc1)[64], int it0, int nkb, uint32_t sbase, int cw,
                                         uint32_t ord_parity) {
  const uint32_t bars = sbase + OFF_BAR;
  const int lane = threadIdx.x & 31;
  int stage = it0 % STAGES;
  uint32_t phase = (it0 / STAGES) & 1;
#pragma unroll
  for (int i = 0; i < 64; i++) { acc0[i] = 0.f; acc1[i] = 0.f; }
  mbar_wait(bars + B_ORD + 8 * cw, ord_parity);
  int prev = 0;
  for (int kb = 0; kb < nkb; kb++) {
    mbar_wait(bars + 8 * stage, phase);
    if (kb == nkb - 1 && (threadIdx.x & 127) == 0) mbar_arrive(bars + B_ORD + 8 * (cw ^ 1));
    const uint32_t lo = ((sbase & 0x3FFFFu) + stage * STAGE_BYTES) >> 4;
    const uint32_t loK = lo | (1u << 16), loM = lo | (512u << 16);
    wgmma_fence();
#pragma unroll
    for (int k = 0; k < 4; k++) {
      if (MODE == 0) {
        const uint64_t dx = desc128(loK + 1024 + 2 * k);
        wgmma_m64n128k16_ss<0, 0>(acc0, desc128(loK + 2 * k), dx, 1);
        wgmma_m64n128k16_ss<0, 0>(acc1, desc128(loK + 512 + 2 * k), dx, 1);
      } else if (MODE == 1) {
        const uint64_t dw = desc128(loM + 128 * k);
        wgmma_m64n128k16_ss<0, 1>(acc0, desc128(loK + 1024 + 2 * k), dw, 1);
        wgmma_m64n128k16_ss<0, 1>(acc1, desc128(loK + 1536 + 2 * k), dw, 1);
      } else {
        const uint64_t dw = desc128(loK + 2 * k);
        wgmma_m64n128k16_ss<1, 0>(acc0, desc128(loM + 1024 + 128 * k), dw, 1);
        wgmma_m64n128k16_ss<1, 0>(acc1, desc128(loM + 1536 + 128 * k), dw, 1);
      }
    }
    wgmma_commit();
    wgmma_wait<1>();
    if (kb > 0 && lane < 2) mbar_arrive_cluster(bars + B_EMPTY + 8 * prev, lane);
    prev = stage;
    if (++stage == STAGES) { stage = 0; phase ^= 1; }
  }
  wgmma_wait<0>();
  if (lane < 2) mbar_arrive_cluster(bars + B_EMPTY + 8 * prev, lane);
  fence_regs(acc0);
  fence_regs(acc1);
}

template <int N>
__device__ __forceinline__ void dual_softmax_n(const float (&p)[N][16], uint32_t (&pos)[N][8], uint32_t (&neg)[N][8]) {
  constexpr float L2E = 1.4426950408889634f;
  float ca[N][2], cb[N][2];
  {
    float mx[N][2], mn[N][2];
#pragma unroll
    for (int i = 0; i < N; i++)
#pragma unroll
      for (int r = 0; r < 2; r++) {
        const int o = 2 * r;
        mx[i][r] = fmaxf(fmaxf(fmaxf(p[i][o], p[i][o + 1]), fmaxf(p[i][4 + o], p[i][5 + o])),
                         fmaxf(fmaxf(p[i][8 + o], p[i][9 + o]), fmaxf(p[i][12 + o], p[i][13 + o])));
        mn[i][r] = fminf(fminf(fminf(p[i][o], p[i][o + 1]), fminf(p[i][4 + o], p[i][5 + o])),
                         fminf(fminf(p[i][8 + o], p[i][9 + o]), fminf(p[i][12 + o], p[i][13 + o])));
      }
#pragma unroll
    for (int o = 1; o <= 2; o <<= 1) {
      float tx[N][2], tn[N][2];
#pragma unroll
      for (int i = 0; i < N; i++)
#pragma unroll
        for (int r = 0; r < 2; r++) { tx[i][r] = __shfl_xor_sync(0xffffffffu, mx[i][r], o); tn[i][r] = __shfl_xor_sync(0xffffffffu, mn[i][r], o); }
#pragma unroll
      for (int i = 0; i < N; i++)
#pragma unroll
        for (int r = 0; r < 2; r++) { mx[i][r] = fmaxf(mx[i][r], tx[i][r]); mn[i][r] = fminf(mn[i][r], tn[i][r]); }
    }
#pragma unroll
    for (int i = 0; i < N; i++)
#pragma unroll
      for (int r = 0; r < 2; r++) { ca[i][r] = -mx[i][r] * L2E; cb[i][r] = mn[i][r] * L2E; }
  }
  float ep[2][16], en[2][16];
  float rp[2], rn[2];
#pragma unroll
  for (int i = 0; i <= N; i++) {
    const int cur = i & 1, prv = cur ^ 1;
    if (i > 0) {
      float sp[2], sn[2];
#pragma unroll
      for (int r = 0; r < 2; r++) {
        const int o = 2 * r;
        sp[r] = ((ep[prv][o] + ep[prv][o + 1]) + (ep[prv][4 + o] + ep[prv][5 + o])) + ((ep[prv][8 + o] + ep[prv][9 + o]) + (ep[prv][12 + o] + ep[prv][13 + o]));
        sn[r] = ((en[prv][o] + en[prv][o + 1]) + (en[prv][4 + o] + en[prv][5 + o])) + ((en[prv][8 + o] + en[prv][9 + o]) + (en[prv][12 + o] + en[prv][13 + o]));
      }
      float t0[2], t1[2];
#pragma unroll
      for (int r = 0; r < 2; r++) { t0[r] = __shfl_xor_sync(0xffffffffu, sp[r], 1); t1[r] = __shfl_xor_sync(0xffffffffu, sn[r], 1); }
      if (i < N) {
#pragma unroll
        for (int e = 0; e < 4; e++) {
          ep[cur][e] = ex2(fmaf(p[i][e], L2E, ca[i][e >> 1])); en[cur][e] = ex2(fmaf(p[i][e], -L2E, cb[i][e >> 1]));
        }
      }
#pragma unroll
      for (int r = 0; r < 2; r++) { sp[r] += t0[r]; sn[r] += t1[r]; }
#pragma unroll
      for (int r = 0; r < 2; r++) { t0[r] = __shfl_xor_sync(0xffffffffu, sp[r], 2); t1[r] = __shfl_xor_sync(0xffffffffu, sn[r], 2); }
      if (i < N) {
#pragma unroll
        for (int e = 4; e < 8; e++) {
          ep[cur][e] = ex2(fmaf(p[i][e], L2E, ca[i][(e >> 1) & 1])); en[cur][e] = ex2(fmaf(p[i][e], -L2E, cb[i][(e >> 1) & 1]));
        }
      }
#pragma unroll
      for (int r = 0; r < 2; r++) { rp[r] = rcp(sp[r] + t0[r]); rn[r] = rcp(sn[r] + t1[r]); }
    } else {
#pragma unroll
      for (int e = 0; e < 8; e++) {
        ep[cur][e] = ex2(fmaf(p[i][e], L2E, ca[i][(e >> 1) & 1])); en[cur][e] = ex2(fmaf(p[i][e], -L2E, cb[i][(e >> 1) & 1]));
      }
    }
#pragma unroll
    for (int j = 0; j < 4; j++) {
      if (i < N && j >= 2) {
#pragma unroll
        for (int e = 4 * j; e < 4 * j + 4; e++) {
          ep[cur][e] = ex2(fmaf(p[i][e], L2E, ca[i][(e >> 1) & 1])); en[cur][e] = ex2(fmaf(p[i][e], -L2E, cb[i][(e >> 1) & 1]));
        }
      }
      if (i > 0) {
#pragma unroll
        for (int r = 0; r < 2; r++) {
          pos[i - 1][2 * j + r] = pack_bf16(ep[prv][4 * j + 2 * r] * rp[r], ep[prv][4 * j + 2 * r + 1] * rp[r]);
          neg[i - 1][2 * j + r] = pack_bf16(en[prv][4 * j + 2 * r] * rn[r], en[prv][4 * j + 2 * r + 1] * rn[r]);
        }
      }
    }
  }
}

struct cplx { float r, i; };
__device__ __forceinline__ cplx cmul(cplx a, cplx b) { return {a.r * b.r - a.i * b.i, a.r * b.i + a.i * b.r}; }
__device__ __forceinline__ cplx cfma(cplx a, cplx b, cplx c) {
  return {fmaf(a.r, b.r, fmaf(-a.i, b.i, c.r)), fmaf(a.r, b.i, fmaf(a.i, b.r, c.i))};
}
__device__ __forceinline__ cplx shfl_up_c(cplx v, int d) {
  return {__shfl_up_sync(0xffffffffu, v.r, d, 4), __shfl_up_sync(0xffffffffu, v.i, d, 4)};
}

struct ChanParams { cplx lam, c2; };

__device__ __forceinline__ ChanParams chan_params(const Params& prm, int p) {
  const float lr = __bfloat162float(prm.lam_re[p]), li = __bfloat162float(prm.lam_im[p]);
  const float dt = __bfloat162float(__float2bfloat16(expf(__bfloat162float(prm.log_dt[p]))));
  const float mag = expf(dt * lr);
  float sn, cs;
  sincosf(dt * li, &sn, &cs);
  ChanParams c;
  c.lam = {mag * cs, mag * sn};
  const float nr = c.lam.r - 1.0f, ni = c.lam.i;
  const float den = lr * lr + li * li;
  c.c2 = {2.0f * (nr * lr + ni * li) / den, 2.0f * (ni * lr - nr * li) / den};
  return c;
}

__device__ __forceinline__ void epi_bu(float (&are)[64], float (&aim)[64], const ChanParams (&cp)[2], const Params& prm,
                                       uint32_t sbase, int G, int chunk, int cw, unsigned epoch) {
  const int lane = threadIdx.x & 31, w = (threadIdx.x & 127) >> 5, q = lane & 3, r8 = lane >> 2;
  cplx E[2] = {{0.f, 0.f}, {0.f, 0.f}};
#pragma unroll
  for (int k8 = 0; k8 < 16; k8++)
#pragma unroll
    for (int e = 0; e < 2; e++)
#pragma unroll
      for (int c = 0; c < 2; c++) E[c] = cfma(cp[c].lam, E[c], cplx{are[4 * k8 + 2 * c + e], aim[4 * k8 + 2 * c + e]});
  TSTAMP(32 + 4 * (threadIdx.x >> 8));
  cplx L32[2], L128[2], prev[2];
#pragma unroll
  for (int c = 0; c < 2; c++) {
    cplx l = cp[c].lam;
#pragma unroll
    for (int s = 0; s < 5; s++) l = cmul(l, l);
    L32[c] = l;
    const cplx l64 = cmul(l, l);
    L128[c] = cmul(l64, l64);
    cplx t = shfl_up_c(E[c], 1);
    if (q >= 1) E[c] = cfma(L32[c], t, E[c]);
    t = shfl_up_c(E[c], 2);
    if (q >= 2) E[c] = cfma(l64, t, E[c]);
    prev[c] = shfl_up_c(E[c], 1);
    if (q == 0) prev[c] = {0.f, 0.f};
  }
  uint4* gE = g_E + (size_t)G * 16 * 64 + 16 * w + r8;
  if (q == 3) {
    st_tagged(gE + chunk * 64, E[0].r, E[0].i, epoch);
    st_tagged(gE + chunk * 64 + 8, E[1].r, E[1].i, epoch);
  }
  cplx V[2][4];
  {
    unsigned long long w0[8], w1[8];
    unsigned pending = 0;
#pragma unroll
    for (int i = 0; i < 8; i++) {
      w0[i] = 0ull; w1[i] = 0ull;
      if (chunk - 1 - 4 * q - (i & 3) >= 0) pending |= 1u << i;
    }
    unsigned spins = 0;
    if (chunk > 0) __nanosleep(300);
    while (true) {
#pragma unroll
      for (int i = 0; i < 8; i++)
        asm volatile("{\n.reg .pred p;\nsetp.ne.u32 p, %3, 0;\n@p ld.relaxed.gpu.global.v2.b64 {%0, %1}, [%2];\n}"
                     : "+l"(w0[i]), "+l"(w1[i]) : "l"(gE + (chunk - 1 - 4 * q - (i & 3)) * 64 + 8 * (i >> 2)), "r"(pending & (1u << i)) : "memory");
#pragma unroll
      for (int i = 0; i < 8; i++)
        if ((unsigned)(w0[i] >> 32) == epoch && (unsigned)(w1[i] >> 32) == epoch) pending &= ~(1u << i);
      if (__all_sync(0xffffffffu, pending == 0)) break;
      __nanosleep(150);
      if (give_up(++spins, 1u << 20)) break;
    }
#pragma unroll
    for (int i = 0; i < 8; i++) V[i >> 2][i & 3] = {__uint_as_float((unsigned)w0[i]), __uint_as_float((unsigned)w1[i])};
  }
  TSTAMP(33 + 4 * (threadIdx.x >> 8));
  cplx s[2];
#pragma unroll
  for (int c = 0; c < 2; c++) {
    cplx Pq = V[c][3];
#pragma unroll
    for (int jj = 2; jj >= 0; jj--) Pq = cfma(L128[c], Pq, V[c][jj]);
    const cplx l256 = cmul(L128[c], L128[c]);
    const cplx l512 = cmul(l256, l256);
    cplx F = {1.f, 0.f};
    cplx G32 = {1.f, 0.f};
    if (q >= 1) { F = l512; G32 = L32[c]; }
    if (q >= 2) { F = cmul(F, l512); G32 = cmul(G32, L32[c]); }
    if (q >= 3) { F = cmul(F, l512); G32 = cmul(G32, L32[c]); }
    Pq = cmul(Pq, F);
#pragma unroll
    for (int o = 1; o <= 2; o <<= 1) {
      Pq.r += __shfl_xor_sync(0xffffffffu, Pq.r, o);
      Pq.i += __shfl_xor_sync(0xffffffffu, Pq.i, o);
    }
    s[c] = cfma(G32, Pq, prev[c]);
  }
  TSTAMP(34 + 4 * (threadIdx.x >> 8));
  if (cw == 1) mbar_wait(sbase + OFF_BAR + B_EBF, 0);
#pragma unroll
  for (int qq = 0; qq < 4; qq++) {
    uint32_t ore[2][4], oim[2][4];
#pragma unroll
    for (int kk = 0; kk < 4; kk++) {
      const int k8 = 4 * qq + kk;
      float hr[2][2], hi[2][2];
#pragma unroll
      for (int e = 0; e < 2; e++)
#pragma unroll
        for (int c = 0; c < 2; c++) {
          s[c] = cfma(cp[c].lam, s[c], cplx{are[4 * k8 + 2 * c + e], aim[4 * k8 + 2 * c + e]});
          hr[c][e] = fmaf(cp[c].c2.r, s[c].r, -cp[c].c2.i * s[c].i);
          hi[c][e] = -fmaf(cp[c].c2.r, s[c].i, cp[c].c2.i * s[c].r);
        }
#pragma unroll
      for (int c = 0; c < 2; c++) {
        ore[c][kk] = pack_bf16(hr[c][0], hr[c][1]);
        oim[c][kk] = pack_bf16(hi[c][0], hi[c][1]);
      }
    }
#pragma unroll
    for (int c = 0; c < 2; c++) {
      const int row = 16 * w + r8 + 8 * c;
      const uint32_t addr = sbase + OFF_PHI + (qq >> 1) * 8192 + row * 128 + ((((qq & 1) * 4 + q) ^ (row & 7)) << 4);
      asm volatile("st.shared.v4.b32 [%0], {%1, %2, %3, %4};" ::"r"(addr), "r"(ore[c][0]), "r"(ore[c][1]), "r"(ore[c][2]), "r"(ore[c][3]) : "memory");
      asm volatile("st.shared.v4.b32 [%0], {%1, %2, %3, %4};" ::"r"(addr + 16384), "r"(oim[c][0]), "r"(oim[c][1]), "r"(oim[c][2]), "r"(oim[c][3]) : "memory");
    }
  }
  TSTAMP(35 + 4 * (threadIdx.x >> 8));
  fence_async_smem();
  wg_bar(1 + cw);
  if ((threadIdx.x & 127) == 0) {
    tma_store_3d(&prm.tmHT, sbase + OFF_PHI, 0, 64 * G, 2 * chunk);
    tma_store_3d(&prm.tmHT, sbase + OFF_PHI + 16384, 0, 1024 + 64 * G, 2 * chunk);
    bulk_commit();
    bulk_wait_all();
    red_relaxed_add(&g_flags.hcnt[chunk * 8], 1);
    mbar_arrive(sbase + OFF_BAR + B_EBF);
  }
}

__device__ __forceinline__ void epi_kv(float (&acc0)[64], float (&acc1)[64], uint32_t sbase, int hp, int wslot, int cw,
                                       unsigned epoch) {
  const int t = threadIdx.x & 127, lane = t & 31, w = t >> 5, q = lane & 3, r8 = lane >> 2;
  const int mi = lane >> 3, rin = lane & 7;
  uint32_t kf[2][2][8];
#pragma unroll
  for (int half = 0; half < 2; half++) {
    float (&a)[64] = half ? acc1 : acc0;
    const int row = half * 64 + w * 16 + (mi & 1) * 8 + rin;
#pragma unroll
    for (int hh = 0; hh < 2; hh++) {
#pragma unroll
      for (int jp = 0; jp < 2; jp++) {
        const int j = 8 + hh * 4 + jp * 2;
        const int chunk = jp * 2 + (mi >> 1);
        const uint32_t addr = sbase + OFF_V + hh * 8192 + row * 64 + ((chunk ^ ((row >> 1) & 3)) << 4);
        stmatrix_x4(addr, pack_bf16(a[4 * j], a[4 * j + 1]), pack_bf16(a[4 * j + 2], a[4 * j + 3]),
                    pack_bf16(a[4 * j + 4], a[4 * j + 5]), pack_bf16(a[4 * j + 6], a[4 * j + 7]));
      }
#pragma unroll
      for (int i = 0; i < 8; i++) kf[half][hh][i] = pack_bf16(a[16 * hh + 2 * i], a[16 * hh + 2 * i + 1]);
    }
  }
  TSTAMP(40 + 8 * cw);
  float pk[4][16];
  wgmma_fence();
#pragma unroll
  for (int hh = 0; hh < 2; hh++)
#pragma unroll
    for (int half = 0; half < 2; half++)
#pragma unroll
      for (int ks = 0; ks < 2; ks++)
        wgmma_m64n32k16_rs<1>(pk[2 * hh + half], kf[half][hh][4 * ks], kf[half][hh][4 * ks + 1], kf[half][hh][4 * ks + 2],
                              kf[half][hh][4 * ks + 3],
                              make_desc(sbase + OFF_WPHI + (wslot + hh) * 2048 + ks * 1024, 512, 512, 2), ks);
  wgmma_commit();
  wgmma_wait<0>();
#pragma unroll
  for (int i = 0; i < 4; i++) fence_regs(pk[i]);

  TSTAMP(41 + 8 * cw);
  float kvacc[2][20];
  uint32_t pos4[4][8], neg4[4][8];
  dual_softmax_n<4>(pk, pos4, neg4);
#pragma unroll
  for (int hh = 0; hh < 2; hh++) {
#pragma unroll
    for (int half = 0; half < 2; half++) {
      const uint32_t (&posx)[8] = pos4[2 * hh + half];
      const uint32_t (&negx)[8] = neg4[2 * hh + half];
      const int row = half * 64 + w * 16 + (mi & 1) * 8 + rin;
      const uint32_t rb = sbase + OFF_PHI + hh * 16384 + row * 128;
#pragma unroll
      for (int jp = 0; jp < 2; jp++) {
        const int c0 = jp * 2 + (mi >> 1);
        stmatrix_x4(rb + ((c0 ^ rin) << 4), posx[4 * jp], posx[4 * jp + 1], posx[4 * jp + 2], posx[4 * jp + 3]);
        stmatrix_x4(rb + (((c0 + 4) ^ rin) << 4), negx[4 * jp], negx[4 * jp + 1], negx[4 * jp + 2], negx[4 * jp + 3]);
      }
    }
    fence_async_smem();
    wg_bar(1 + cw);
    wgmma_fence();
#pragma unroll
    for (int ks = 0; ks < 8; ks++) {
      const uint32_t vb = sbase + OFF_V + hh * 8192 + ks * 1024;
      wgmma_m64n40k16_ss<1, 1>(kvacc[hh], make_desc(sbase + OFF_PHI + hh * 16384 + ks * 2048, 1024, 1024, 1),
                               make_desc(vb, sbase + OFF_ONES - vb, 512, 2), ks);
    }
    wgmma_commit();
  }
  TSTAMP(42 + 8 * cw);
  wgmma_wait<0>();
  fence_regs(kvacc[0]);
  fence_regs(kvacc[1]);
  TSTAMP(43 + 8 * cw);
  wg_bar(1 + cw);
#pragma unroll
  for (int hh = 0; hh < 2; hh++) {
    const uint32_t dst = sbase + OFF_PHI + hh * 16384 + ((16 * w + r8) * KVW + 2 * q) * 4;
#pragma unroll
    for (int j = 0; j < 5; j++) {
      asm volatile("st.shared.v2.f32 [%0], {%1, %2};" ::"r"(dst + 32 * j), "f"(kvacc[hh][4 * j]), "f"(kvacc[hh][4 * j + 1]) : "memory");
      asm volatile("st.shared.v2.f32 [%0], {%1, %2};" ::"r"(dst + 8 * KVW * 4 + 32 * j), "f"(kvacc[hh][4 * j + 2]), "f"(kvacc[hh][4 * j + 3]) : "memory");
    }
  }
  fence_async_smem();
  wg_bar(1 + cw);
  TSTAMP(44 + 8 * cw);
  if (t == 0) {
    wait_ge(&g_flags.zero_cnt, 128u * epoch);
    bulk_reduce_f32(g_kv + (size_t)(2 * hp) * 64 * KVW, sbase + OFF_PHI, 64 * KVW * 4);
    bulk_reduce_f32(g_kv + (size_t)(2 * hp + 1) * 64 * KVW, sbase + OFF_PHI + 16384, 64 * KVW * 4);
    bulk_commit();
    bulk_wait_all();
    red_relaxed_add(&g_flags.kvcnt[hp * 8], 1);
    mbar_arrive(sbase + OFF_BAR + B_EBF);
    if (cw == 1) mbar_arrive(sbase + OFF_BAR + B_E3);
  }
  TSTAMP(45 + 8 * cw);
}

__device__ __forceinline__ void q_issue_pq(float (&pq)[16], uint32_t sbase, int item) {
  const int half = item & 1, hs = item >> 1;
  const uint32_t a = sbase + OFF_PHI + (hs >> 1) * 16384 + half * 8192 + (hs & 1) * 64;
  const uint32_t b = sbase + OFF_WPHI + hs * 2048;
  wgmma_fence();
  wgmma_m64n32k16_ss<0, 1>(pq, make_desc(a, 16, 1024, 1), make_desc(b, 512, 512, 2), 0);
  wgmma_m64n32k16_ss<0, 1>(pq, make_desc(a + 32, 16, 1024, 1), make_desc(b + 1024, 512, 512, 2), 1);
  wgmma_commit();
}
__device__ __forceinline__ void q_issue_num(float (&num)[20], const uint32_t (&pos)[8], const uint32_t (&neg)[8], uint32_t sbase, int item) {
  const uint32_t b = sbase + OFF_V + (item >> 1) * 5120;
  wgmma_fence();
  wgmma_m64n40k16_rs<1>(num, pos[0], pos[1], pos[2], pos[3], make_desc(b, 640, 128, 0), 0);
  wgmma_m64n40k16_rs<1>(num, pos[4], pos[5], pos[6], pos[7], make_desc(b + 1280, 640, 128, 0), 1);
  wgmma_m64n40k16_rs<1>(num, neg[0], neg[1], neg[2], neg[3], make_desc(b + 2560, 640, 128, 0), 1);
  wgmma_m64n40k16_rs<1>(num, neg[4], neg[5], neg[6], neg[7], make_desc(b + 3840, 640, 128, 0), 1);
  wgmma_commit();
}
__device__ __forceinline__ void q_store_o(const float (&num)[20], uint32_t sbase, int item) {
  const int lane = threadIdx.x & 31, w = (threadIdx.x & 127) >> 5, mi = lane >> 3, rin = lane & 7;
  const int half = item & 1, hs = item >> 1;
  const float d0 = __shfl_sync(0xffffffffu, num[16], lane & ~3), d1 = __shfl_sync(0xffffffffu, num[18], lane & ~3);
  const float i0 = __fdividef(1.0f, d0 + 1e-6f), i1 = __fdividef(1.0f, d1 + 1e-6f);
  const int row = half * 64 + w * 16 + (mi & 1) * 8 + rin;
  const uint32_t rb = sbase + OFF_PHI + (hs >> 1) * 16384 + row * 128;
#pragma unroll
  for (int jp = 0; jp < 2; jp++) {
    const int c0 = (hs & 1) * 4 + jp * 2 + (mi >> 1);
    stmatrix_x4(rb + ((c0 ^ rin) << 4), pack_bf16(num[8 * jp] * i0, num[8 * jp + 1] * i0),
                pack_bf16(num[8 * jp + 2] * i1, num[8 * jp + 3] * i1), pack_bf16(num[8 * jp + 4] * i0, num[8 * jp + 5] * i0),
                pack_bf16(num[8 * jp + 6] * i1, num[8 * jp + 7] * i1));
  }
}
__device__ __forceinline__ void epi_q(float (&acc0)[64], float (&acc1)[64], const Params& prm, uint32_t sbase, int g, int rb_idx) {
  const int t = threadIdx.x & 127, lane = t & 31, w = t >> 5;
  const int mi = lane >> 3, rin = lane & 7;
  {
    const int row = w * 16 + (mi & 1) * 8 + rin;
#pragma unroll
    for (int jp = 0; jp < 8; jp++) {
      const int j = 2 * jp, c0 = (j & 7) + (mi >> 1);
      const uint32_t addr = sbase + OFF_PHI + (j >> 3) * 16384 + row * 128 + ((c0 ^ rin) << 4);
      stmatrix_x4(addr, pack_bf16(acc0[4 * j], acc0[4 * j + 1]), pack_bf16(acc0[4 * j + 2], acc0[4 * j + 3]),
                  pack_bf16(acc0[4 * j + 4], acc0[4 * j + 5]), pack_bf16(acc0[4 * j + 6], acc0[4 * j + 7]));
      stmatrix_x4(addr + 8192, pack_bf16(acc1[4 * j], acc1[4 * j + 1]), pack_bf16(acc1[4 * j + 2], acc1[4 * j + 3]),
                  pack_bf16(acc1[4 * j + 4], acc1[4 * j + 5]), pack_bf16(acc1[4 * j + 6], acc1[4 * j + 7]));
    }
  }
  fence_async_smem();
  wg_bar(1);
  TSTAMP(56);
#pragma unroll 1
  for (int it = 0; it < 8; it += 4) {
    float pq[4][16], num[4][20];
    uint32_t pos[4][8], neg[4][8];
    QT(0);
#pragma unroll
    for (int i = 0; i < 4; i++) q_issue_pq(pq[i], sbase, it + i);
    wgmma_wait<0>();
#pragma unroll
    for (int i = 0; i < 4; i++) fence_regs(pq[i]);
    QT(1);
    dual_softmax_n<4>(pq, pos, neg);
    QT(2);
    mbar_wait(sbase + OFF_BAR + B_KVX + 8 * (it >> 2), 0);
    if (it == 0) TSTAMP(57);
    if (it == 4) TSTAMP(58);
    QT(3);
#pragma unroll
    for (int i = 0; i < 4; i++) q_issue_num(num[i], pos[i], neg[i], sbase, it + i);
    QT(4);
    wgmma_wait<2>();
    fence_regs(num[0]); fence_regs(num[1]);
    QT(5);
    q_store_o(num[0], sbase, it);
    q_store_o(num[1], sbase, it + 1);
    wgmma_wait<0>();
    fence_regs(num[2]); fence_regs(num[3]);
    QT(6);
    q_store_o(num[2], sbase, it + 2);
    q_store_o(num[3], sbase, it + 3);
    QT(7);
  }
  TSTAMP(60);
  fence_async_smem();
  wg_bar(1);
  if (t == 0) {
    tma_store_2d(&prm.tmO, sbase + OFF_PHI, 64 * g, 128 * rb_idx);
    tma_store_2d(&prm.tmO, sbase + OFF_PHI + 16384, 64 * (g + 8), 128 * rb_idx);
    bulk_commit();
    bulk_wait_all();
    red_relaxed_add(&g_flags.ocnt[rb_idx * 8], 1);
  }
}

__device__ __forceinline__ void helper_kv(uint32_t sbase, int g, unsigned epoch) {
  const int h = threadIdx.x - 32;
  mbar_wait_sleep(sbase + OFF_BAR + B_E3, 0);
#pragma unroll 1
  for (int pr = 0; pr < 2; pr++) {
    if ((h & 31) == 0) wait_ge(&g_flags.kvcnt[(g + 8 * pr) * 8], 16u * epoch);
    __syncwarp();
    const float4* src = reinterpret_cast<const float4*>(g_kv + (size_t)(2 * g + 16 * pr) * 64 * KVW);
#pragma unroll 1
    for (int ib = 0; ib < 2; ib++) {
      float4 u[7];
#pragma unroll
      for (int i = 0; i < 7; i++) u[i] = __ldcg(src + min((ib * 7 + i) * 96 + h, 1279));
#pragma unroll
      for (int i = 0; i < 7; i++) {
        const int idx = min((ib * 7 + i) * 96 + h, 1279);
        const int f2 = idx / 10, j = idx - f2 * 10;
        const uint32_t dst = sbase + OFF_V + pr * 10240 + (f2 >> 3) * 640 + (j >> 1) * 128 + (f2 & 7) * 16 + (j & 1) * 8;
        asm volatile("st.shared.v2.b32 [%0], {%1, %2};" ::"r"(dst), "r"(pack_bf16(u[i].x, u[i].y)), "r"(pack_bf16(u[i].z, u[i].w)) : "memory");
      }
    }
    fence_async_smem();
    __syncwarp();
    if ((h & 31) == 0) mbar_arrive(sbase + OFF_BAR + B_KVX + 8 * pr);
  }
}

__device__ __forceinline__ float bf16_round(float x) { return __bfloat162float(__float2bfloat16(x)); }
__device__ __forceinline__ void store_out(const float (&a)[64], float* dst) {
#pragma unroll
  for (int j = 0; j < 16; j++) {
    __stcs(reinterpret_cast<float2*>(dst + 8 * j), make_float2(bf16_round(a[4 * j]), bf16_round(a[4 * j + 1])));
    __stcs(reinterpret_cast<float2*>(dst + 8 * 2048 + 8 * j), make_float2(bf16_round(a[4 * j + 2]), bf16_round(a[4 * j + 3])));
  }
}
__device__ __forceinline__ void store_y(const float (&a)[64], const Params& prm, int rb, int g, int m0, int q) {
  const __nv_bfloat162* dk = reinterpret_cast<const __nv_bfloat162*>(prm.dskip + 128 * g + 2 * q);
#pragma unroll
  for (int h = 0; h < 2; h++) {
    const int m = m0 + 8 * h;
    const int tt = rb * 128 + 32 * ((m >> 3) & 3) + 8 * (m >> 5) + (m & 7);
    const __nv_bfloat162* xr = reinterpret_cast<const __nv_bfloat162*>(prm.xB + (size_t)tt * DM + 128 * g + 2 * q);
    float* dst = prm.out + (size_t)tt * 2048 + 1024 + 128 * g + 2 * q;
#pragma unroll
    for (int j = 0; j < 16; j++) {
      const float2 sk = __bfloat1622float2(__hmul2(__ldg(xr + 4 * j), __ldg(dk + 4 * j)));
      __stcs(reinterpret_cast<float2*>(dst + 8 * j), make_float2(a[4 * j + 2 * h] + sk.x, a[4 * j + 2 * h + 1] + sk.y));
    }
  }
}

__global__ void __launch_bounds__(384, 1) fused_kernel(const __grid_constant__ Params prm) {
  extern __shared__ uint8_t smem_raw[];
  const uint32_t sbase = (smem_u32(smem_raw) + 1023) & ~1023u;
  const uint32_t bars = sbase + OFF_BAR;
  const int tid = threadIdx.x, wg = __shfl_sync(0xffffffffu, tid >> 7, 0);
  const int cl = blockIdx.x >> 1, rank = blockIdx.x & 1;
  const int g = cl >> 3, rb = 2 * (cl & 7) + rank;

  if (tid == 0) {
    for (int s = 0; s < STAGES; s++) { mbar_init(bars + 8 * s, 1);
      mbar_init(bars + B_EMPTY + 8 * s, 8);
    }
    mbar_init(bars + B_ORD, 1); mbar_init(bars + B_ORD + 8, 1); mbar_init(bars + B_EBF, 1); mbar_init(bars + B_WPHI, 1); mbar_init(bars + B_EPOCH, 1); mbar_init(bars + B_KVX, 3); mbar_init(bars + B_KVX + 8, 3); mbar_init(bars + B_E3, 1);
    asm volatile("fence.mbarrier_init.release.cluster;" ::: "memory");
  } else if (tid == 32) {
    prefetch_tm(&prm.tmXB); prefetch_tm(rank ? &prm.tmBim : &prm.tmBre); prefetch_tm(&prm.tmWphi);
    prefetch_tm(&prm.tmXA); prefetch_tm(&prm.tmWqkv); prefetch_tm(&prm.tmHT);
    prefetch_tm(&prm.tmCre); prefetch_tm(&prm.tmCim); prefetch_tm(&prm.tmO); prefetch_tm(&prm.tmWo);
  } else if (tid >= 64 && tid < 128) {
    asm volatile("st.shared.v4.b32 [%0], {%1, %2, %2, %2};" ::"r"(sbase + OFF_ONES + (tid - 64) * 16), "r"(0x00003F80u), "r"(0u) : "memory");
    fence_async_smem();
  }
  __syncthreads();
  asm volatile("barrier.cluster.arrive.relaxed.aligned;\nbarrier.cluster.wait.acquire.aligned;" ::: "memory");

  if (wg == 0) {
    reg_dealloc<56>();
    const int warp = tid >> 5, lane = tid & 31;
    if (warp == 0) {
      if (lane == 0) {
        TSTAMP(0);
        mbar_expect_tx(bars + B_WPHI, 8192);
        tma_2d(sbase + OFF_WPHI, &prm.tmWphi, 0, 64 * g, bars + B_WPHI);
        tma_2d(sbase + OFF_WPHI + 4096, &prm.tmWphi, 0, 64 * g + 512, bars + B_WPHI);
        int stage = 0;
        uint32_t phase = 1;
        unsigned epoch = 0;
        for (int tile = 0; tile < 7; tile++) {
          const int nkb = (tile == 5) ? 32 : 16;
          if (tile == 5) {
            mbar_wait(bars + B_EPOCH, 0);
            asm volatile("ld.shared.u32 %0, [%1];" : "=r"(epoch) : "r"(bars + B_EPOCHV) : "memory");
            wait_ge(&g_flags.hcnt[rb * 8], 16u * epoch);
          } else if (tile == 6) {
            wait_ge(&g_flags.ocnt[rb * 8], 8u * epoch);
          }
          for (int kb = 0; kb < nkb; kb++) {
            mbar_wait(bars + B_EMPTY + 8 * stage, phase);
            const uint32_t full = bars + 8 * stage;
            const uint32_t sw = sbase + stage * STAGE_BYTES, sx = sw + 16384, swr = sw + rank * 8192;
            mbar_expect_tx(full, STAGE_BYTES);
            if (tile < 2) {
              tma_2d_mc(swr, rank ? &prm.tmBim : &prm.tmBre, kb * 64, 64 * (g + 8 * tile), full);
              tma_5d(sx, &prm.tmXB, kb * 64, 0, 0, 0, rb, full);
            } else if (tile < 4) {
              tma_2d_mc(swr, &prm.tmWqkv, 1024 + rank * 1024 + 64 * (g + 8 * (tile - 2)), kb * 64, full);
              tma_2d(sx, &prm.tmXA, kb * 64, rb * 128, full);
            } else if (tile == 4) {
              tma_2d_mc(swr, &prm.tmWqkv, 64 * (g + 8 * rank), kb * 64, full);
              tma_2d(sx, &prm.tmXA, kb * 64, rb * 128, full);
            } else if (tile == 5) {
              tma_2d_mc(swr, kb < 16 ? &prm.tmCre : &prm.tmCim, (kb & 15) * 64, 128 * g + 64 * rank, full);
              tma_3d(sx, &prm.tmHT, 0, kb * 64, 2 * rb, full);
            } else {
              tma_2d_mc(swr, &prm.tmWo, 128 * g + 64 * rank, kb * 64, full);
              tma_2d(sx, &prm.tmO, kb * 64, rb * 128, full);
            }
            if (++stage == STAGES) { stage = 0; phase ^= 1; }
          }
        }
        TSTAMP(1);
      }
    } else {
      unsigned epoch = 0;
      if (warp == 1) {
      if (lane == 0) {
        epoch = (atomicAdd(&g_flags.ticket, 1u) >> 7) + 1u;
        asm volatile("st.shared.u32 [%0], %1;" ::"r"(bars + B_EPOCHV), "r"(epoch) : "memory");
        mbar_arrive(bars + B_EPOCH);
      }
      uint4* z = reinterpret_cast<uint4*>(g_kv) + blockIdx.x * 160;
#pragma unroll
      for (int i = 0; i < 5; i++) __stcg(z + i * 32 + lane, make_uint4(0, 0, 0, 0));
      __syncwarp();
      if (lane == 0) red_release_add(&g_flags.zero_cnt, 1);
      }
      mbar_wait(bars + B_EPOCH, 0);
      asm volatile("ld.shared.u32 %0, [%1];" : "=r"(epoch) : "r"(bars + B_EPOCHV) : "memory");
      helper_kv(sbase, g, epoch);
    }
    __syncwarp();
    asm volatile("barrier.cluster.arrive.relaxed.aligned;\nbarrier.cluster.wait.aligned;" ::: "memory");
  } else {
    reg_alloc<224>();
    const int cw = wg - 1;
    const int t = tid & 127, lane = t & 31, w = t >> 5, q = lane & 3, r8 = lane >> 2;
    float acc0[64], acc1[64];
    unsigned epoch;
    {
      const int G = g + 8 * cw;
      ChanParams cp[2];
      cp[0] = chan_params(prm, 64 * G + 16 * w + r8);
      cp[1] = chan_params(prm, 64 * G + 16 * w + r8 + 8);
      TSTAMP(2 + 12 * cw);
      mainloop<0>(acc0, acc1, 16 * cw, 16, sbase, cw, cw ^ 1);
      TSTAMP(3 + 12 * cw);
      mbar_wait(bars + B_EPOCH, 0);
      asm volatile("ld.shared.u32 %0, [%1];" : "=r"(epoch) : "r"(bars + B_EPOCHV) : "memory");
      epi_bu(acc0, acc1, cp, prm, sbase, G, rb, cw, epoch);
      TSTAMP(4 + 12 * cw);
    }
    {
      mainloop<1>(acc0, acc1, 32 + 16 * cw, 16, sbase, cw, cw);
      TSTAMP(5 + 12 * cw);
      mbar_wait(bars + B_WPHI, 0);
      mbar_wait(bars + B_EBF, cw ^ 1);
      epi_kv(acc0, acc1, sbase, g + 8 * cw, 2 * cw, cw, epoch);
      TSTAMP(6 + 12 * cw);
    }
    if (cw == 0) {
      mainloop<1>(acc0, acc1, 64, 16, sbase, 0, 1);
      TSTAMP(7);
      mbar_wait(bars + B_EBF, 1);
      epi_q(acc0, acc1, prm, sbase, g, rb);
      TSTAMP(8);
      mainloop<1>(acc0, acc1, 112, 16, sbase, 0, 0);
      TSTAMP(9);
      float* dst = prm.out + (size_t)(rb * 128 + 16 * w + r8) * 2048 + 128 * g + 2 * q;
      store_out(acc0, dst);
      store_out(acc1, dst + (size_t)64 * 2048);
      TSTAMP(10);
    } else {
      mainloop<2>(acc0, acc1, 80, 32, sbase, 1, 0);
      TSTAMP(19);
      store_y(acc0, prm, rb, g, 16 * w + r8, q);
      store_y(acc1, prm, rb, g, 16 * w + r8 + 64, q);
      TSTAMP(20);
    }
    asm volatile("barrier.cluster.arrive.relaxed.aligned;\nbarrier.cluster.wait.aligned;" ::: "memory");
  }
}

typedef CUresult (*PFN_encodeTiled)(CUtensorMap*, CUtensorMapDataType, cuuint32_t, void*, const cuuint64_t*, const cuuint64_t*,
                                    const cuuint32_t*, const cuuint32_t*, CUtensorMapInterleave, CUtensorMapSwizzle,
                                    CUtensorMapL2promotion, CUtensorMapFloatOOBfill);

bool make_tm(PFN_encodeTiled enc, CUtensorMap* tm, const void* base, int rank, const uint64_t* dims, const uint64_t* strides,
             const uint32_t* box, CUtensorMapSwizzle sw) {
  cuuint64_t gd[5], gs[5];
  cuuint32_t bx[5], es[5];
  for (int i = 0; i < rank; i++) { gd[i] = dims[i]; bx[i] = box[i]; es[i] = 1; }
  for (int i = 0; i + 1 < rank; i++) gs[i] = strides[i];
  return enc(tm, CU_TENSOR_MAP_DATA_TYPE_BFLOAT16, rank, const_cast<void*>(base), gd, gs, bx, es, CU_TENSOR_MAP_INTERLEAVE_NONE, sw,
             CU_TENSOR_MAP_L2_PROMOTION_L2_256B, CU_TENSOR_MAP_FLOAT_OOB_FILL_NONE) == CUDA_SUCCESS;
}
bool make_tm2(PFN_encodeTiled enc, CUtensorMap* tm, const void* base, uint64_t inner, uint64_t outer, uint32_t b0, uint32_t b1,
              CUtensorMapSwizzle sw = CU_TENSOR_MAP_SWIZZLE_128B) {
  const uint64_t dims[2] = {inner, outer}, str[1] = {inner * 2};
  const uint32_t box[2] = {b0, b1};
  return make_tm(enc, tm, base, 2, dims, str, box, sw);
}

}

extern "C" void kernel_launch(void* const* d_in, const int* in_sizes, int n_in, void* d_out, int out_size) {
  (void)in_sizes; (void)n_in; (void)out_size;
  static PFN_encodeTiled enc = nullptr;
  static void *pHT = nullptr, *pO = nullptr;
  if (!enc) {
    void* fn = nullptr;
    cudaDriverEntryPointQueryResult qr;
    if (cudaGetDriverEntryPoint("cuTensorMapEncodeTiled", &fn, cudaEnableDefault, &qr) != cudaSuccess || !fn) return;
    enc = (PFN_encodeTiled)fn;
    cudaFuncSetAttribute(fused_kernel, cudaFuncAttributeMaxDynamicSharedMemorySize, SMEM_BYTES);
    cudaGetSymbolAddress(&pHT, g_HT);
    cudaGetSymbolAddress(&pO, g_O);
  }
  Params prm;
  bool ok = true;
  {
    const uint64_t dims[5] = {1024, 2, 4, 16, 16}, str[4] = {2048, 65536, 4096, 262144};
    const uint32_t box[5] = {64, 2, 4, 16, 1};
    ok &= make_tm(enc, &prm.tmXB, d_in[4], 5, dims, str, box, CU_TENSOR_MAP_SWIZZLE_128B);
  }
  ok &= make_tm2(enc, &prm.tmBre, d_in[7], 1024, 1024, 64, 64);
  ok &= make_tm2(enc, &prm.tmBim, d_in[8], 1024, 1024, 64, 64);
  ok &= make_tm2(enc, &prm.tmXA, d_in[0], 1024, 2048, 64, 128);
  ok &= make_tm2(enc, &prm.tmWqkv, d_in[1], 3072, 1024, 64, 64);
  ok &= make_tm2(enc, &prm.tmWphi, d_in[2], 32, 1024, 32, 64, CU_TENSOR_MAP_SWIZZLE_64B);
  {
    const uint64_t dims[3] = {64, 2048, 32}, str[2] = {4096, 128};
    const uint32_t box[3] = {64, 64, 2};
    ok &= make_tm(enc, &prm.tmHT, pHT, 3, dims, str, box, CU_TENSOR_MAP_SWIZZLE_128B);
  }
  ok &= make_tm2(enc, &prm.tmCre, d_in[9], 1024, 1024, 64, 64);
  ok &= make_tm2(enc, &prm.tmCim, d_in[10], 1024, 1024, 64, 64);
  ok &= make_tm2(enc, &prm.tmO, pO, 1024, 2048, 64, 128);
  ok &= make_tm2(enc, &prm.tmWo, d_in[3], 1024, 1024, 64, 64);
  if (!ok) return;
  prm.xB = (const __nv_bfloat16*)d_in[4];
  prm.lam_re = (const __nv_bfloat16*)d_in[5];
  prm.lam_im = (const __nv_bfloat16*)d_in[6];
  prm.log_dt = (const __nv_bfloat16*)d_in[11];
  prm.dskip = (const __nv_bfloat16*)d_in[12];
  prm.out = (float*)d_out;

  cudaLaunchConfig_t cfg = {};
  cfg.gridDim = dim3(128);
  cfg.blockDim = dim3(384);
  cfg.dynamicSmemBytes = SMEM_BYTES;
  cfg.stream = cudaStreamPerThread;
  cudaLaunchAttribute attr[1];
  attr[0].id = cudaLaunchAttributeClusterDimension;
  attr[0].val.clusterDim.x = 2; attr[0].val.clusterDim.y = 1; attr[0].val.clusterDim.z = 1;
  cfg.attrs = attr;
  cfg.numAttrs = 1;
  cudaLaunchKernelEx(&cfg, fused_kernel, prm);
}
```

```cpp
#include <cuda_runtime.h>
#include <cuda_bf16.h>
#include <cuda.h>
#include <stdint.h>

namespace {

constexpr int SEQ = 2048;
constexpr int DM = 1024;
#define NSTAGES 5
constexpr int STAGES = NSTAGES;
constexpr int STAGE_BYTES = 32768;
constexpr int OFF_EB = 5 * STAGE_BYTES;
constexpr int OFF_PHI = OFF_EB;
constexpr int OFF_V = OFF_EB + 32768;
constexpr int OFF_WPHI = OFF_EB + 53248;
constexpr int OFF_ONES = OFF_EB + 61440;
constexpr int OFF_BAR = OFF_EB + 62464;
constexpr int SMEM_BYTES = OFF_BAR + 256 + 1024;
constexpr int B_EMPTY = 64, B_ORD = 128, B_EBF = 144, B_WPHI = 152, B_EPOCH = 160, B_KVX = 168  , B_E3 = 184, B_EPOCHV = 192, B_DEAD = 196, B_JOB = 200  , B_PARAM = 248;

constexpr int KVW = 40;

struct Params {
  CUtensorMap tmXB;
  CUtensorMap tmBre, tmBim;
  CUtensorMap tmXA;
  CUtensorMap tmWqkv;
  CUtensorMap tmWphi;
  CUtensorMap tmHT;
  CUtensorMap tmCre, tmCim;
  CUtensorMap tmO;
  CUtensorMap tmWo;
  const __nv_bfloat16* xB;
  const __nv_bfloat16* lam_re;
  const __nv_bfloat16* lam_im;
  const __nv_bfloat16* log_dt;
  const __nv_bfloat16* dskip;
  float* out;
};

__device__ __nv_bfloat16 g_HT[2048 * 2048];
__device__ __nv_bfloat16 g_O[SEQ * DM];
__device__ float g_kv[32 * 64 * KVW];
__device__ uint4 g_E[16 * 16 * 64];
struct Flags {
  unsigned ticket;   unsigned pad0[31];
  unsigned zero_cnt; unsigned pad1[31];
  unsigned hcnt[16 * 8];
  unsigned kvcnt[16 * 8];
  unsigned ocnt[2 * 16 * 8];
};
__device__ Flags g_flags;
#define TSTAMP(i)
#define QT(i)

__device__ __forceinline__ uint32_t smem_u32(const void* p) { return (uint32_t)__cvta_generic_to_shared(p); }
__device__ __forceinline__ void mbar_init(uint32_t bar, uint32_t count) {
  asm volatile("mbarrier.init.shared::cta.b64 [%0], %1;" ::"r"(bar), "r"(count));
}
__device__ __forceinline__ void mbar_expect_tx(uint32_t bar, uint32_t bytes) {
  asm volatile("mbarrier.arrive.expect_tx.shared::cta.b64 _, [%0], %1;" ::"r"(bar), "r"(bytes) : "memory");
}
__device__ __forceinline__ void mbar_arrive(uint32_t bar) {
  asm volatile("mbarrier.arrive.shared::cta.b64 _, [%0];" ::"r"(bar) : "memory");
}
__device__ __forceinline__ void mbar_arrive_cluster(uint32_t bar, uint32_t cta) {
  asm volatile("{\n.reg .b32 ra;\nmapa.shared::cluster.u32 ra, %0, %1;\nmbarrier.arrive.shared::cluster.b64 _, [ra];\n}" ::"r"(bar), "r"(cta) : "memory");
}
__device__ __forceinline__ uint32_t dead_addr(uint32_t bar) { return (bar & ~0xFFu) + B_DEAD; }
__device__ __forceinline__ void mbar_wait(uint32_t bar, uint32_t parity) {
  asm volatile(
      "{\n.reg .pred p;\n.reg .u32 c, d;\n"
      "mov.u32 c, 0;\n"
      "WAIT_LOOP:\n"
      "mbarrier.try_wait.parity.shared::cta.b64 p, [%0], %1;\n"
      "@p bra WAIT_DONE;\n"
      "add.u32 c, c, 1;\n"
      "setp.gt.u32 p, c, 0x200000;\n"
      "@p st.volatile.shared.u32 [%2], c;\n"
      "ld.volatile.shared.u32 d, [%2];\n"
      "setp.eq.u32 p, d, 0;\n"
      "@p bra WAIT_LOOP;\n"
      "WAIT_DONE:\n}\n" ::"r"(bar), "r"(parity), "r"(dead_addr(bar)) : "memory");
}
__device__ __forceinline__ bool give_up(uint32_t bars, unsigned spins) {
  unsigned d;
  if (spins > (1u << 20)) asm volatile("st.volatile.shared.u32 [%0], %1;" ::"r"(bars + B_DEAD), "r"(spins) : "memory");
  asm volatile("ld.volatile.shared.u32 %0, [%1];" : "=r"(d) : "r"(bars + B_DEAD) : "memory");
  return d != 0;
}
__device__ __forceinline__ unsigned ld_relaxed(const unsigned* p) {
  unsigned v;
  asm volatile("ld.relaxed.gpu.global.u32 %0, [%1];" : "=r"(v) : "l"(p) : "memory");
  return v;
}
__device__ __forceinline__ void wait_ge(uint32_t bars, const unsigned* p, unsigned target) {
  unsigned spins = 0;
  while ((int)(ld_relaxed(p) - target) < 0) {
    __nanosleep(128);
    if (give_up(bars, ++spins)) break;
  }
}
__device__ __forceinline__ void red_release_add(unsigned* p, unsigned v) {
  asm volatile("red.release.gpu.global.add.u32 [%0], %1;" ::"l"(p), "r"(v) : "memory");
}
__device__ __forceinline__ void red_relaxed_add(unsigned* p, unsigned v) {
  asm volatile("red.relaxed.gpu.global.add.u32 [%0], %1;" ::"l"(p), "r"(v) : "memory");
}
__device__ __forceinline__ void st_tagged(uint4* p, float a, float b, unsigned tag) {
  const unsigned long long w0 = ((unsigned long long)tag << 32) | __float_as_uint(a);
  const unsigned long long w1 = ((unsigned long long)tag << 32) | __float_as_uint(b);
  asm volatile("st.relaxed.gpu.global.v2.b64 [%0], {%1, %2};" ::"l"(p), "l"(w0), "l"(w1) : "memory");
}
__device__ __forceinline__ void bulk_commit() { asm volatile("cp.async.bulk.commit_group;" ::: "memory"); }
__device__ __forceinline__ void bulk_wait_read() { asm volatile("cp.async.bulk.wait_group.read 0;" ::: "memory"); }
__device__ __forceinline__ void bulk_wait_all() { asm volatile("cp.async.bulk.wait_group 0;" ::: "memory"); }
__device__ __forceinline__ void bulk_reduce_f32(float* dst, uint32_t src, uint32_t bytes) {
  asm volatile("cp.reduce.async.bulk.global.shared::cta.bulk_group.add.f32 [%0], [%1], %2;" ::"l"(dst), "r"(src), "r"(bytes) : "memory");
}
__device__ __forceinline__ void tma_store_3d(const CUtensorMap* tm, uint32_t src, int c0, int c1, int c2) {
  asm volatile("cp.async.bulk.tensor.3d.global.shared::cta.bulk_group [%0, {%2, %3, %4}], [%1];"
               ::"l"(tm), "r"(src), "r"(c0), "r"(c1), "r"(c2) : "memory");
}
__device__ __forceinline__ void fence_async_smem() { asm volatile("fence.proxy.async.shared::cta;" ::: "memory"); }
__device__ __forceinline__ void tma_2d(uint32_t dst, const CUtensorMap* tm, int c0, int c1, uint32_t bar) {
  asm volatile("cp.async.bulk.tensor.2d.shared::cluster.global.mbarrier::complete_tx::bytes [%0], [%1, {%3, %4}], [%2];"
               ::"r"(dst), "l"(tm), "r"(bar), "r"(c0), "r"(c1) : "memory");
}
__device__ __forceinline__ void tma_3d(uint32_t dst, const CUtensorMap* tm, int c0, int c1, int c2, uint32_t bar) {
  asm volatile("cp.async.bulk.tensor.3d.shared::cluster.global.mbarrier::complete_tx::bytes [%0], [%1, {%3, %4, %5}], [%2];"
               ::"r"(dst), "l"(tm), "r"(bar), "r"(c0), "r"(c1), "r"(c2) : "memory");
}
__device__ __forceinline__ void tma_5d(uint32_t dst, const CUtensorMap* tm, int c0, int c1, int c2, int c3, int c4, uint32_t bar) {
  asm volatile("cp.async.bulk.tensor.5d.shared::cluster.global.mbarrier::complete_tx::bytes [%0], [%1, {%3, %4, %5, %6, %7}], [%2];"
               ::"r"(dst), "l"(tm), "r"(bar), "r"(c0), "r"(c1), "r"(c2), "r"(c3), "r"(c4) : "memory");
}
__device__ __forceinline__ void tma_2d_mc(uint32_t dst, const CUtensorMap* tm, int c0, int c1, uint32_t bar) {
  asm volatile("cp.async.bulk.tensor.2d.shared::cluster.global.mbarrier::complete_tx::bytes.multicast::cluster [%0], [%1, {%3, %4}], [%2], %5;"
               ::"r"(dst), "l"(tm), "r"(bar), "r"(c0), "r"(c1), "h"((uint16_t)3) : "memory");
}
__device__ __forceinline__ void tma_store_2d(const CUtensorMap* tm, uint32_t src, int c0, int c1) {
  asm volatile("cp.async.bulk.tensor.2d.global.shared::cta.bulk_group [%0, {%2, %3}], [%1];"
               ::"l"(tm), "r"(src), "r"(c0), "r"(c1) : "memory");
}
__device__ __forceinline__ void prefetch_tm(const CUtensorMap* tm) {
  asm volatile("prefetch.tensormap [%0];" ::"l"(tm) : "memory");
}
__device__ __forceinline__ void wgmma_fence() { asm volatile("wgmma.fence.sync.aligned;" ::: "memory"); }
__device__ __forceinline__ void wgmma_commit() { asm volatile("wgmma.commit_group.sync.aligned;" ::: "memory"); }
template <int N> __device__ __forceinline__ void wgmma_wait() { asm volatile("wgmma.wait_group.sync.aligned %0;" ::"n"(N) : "memory"); }
__device__ __forceinline__ void wg_bar(int id) {
  if (id == 1) asm volatile("bar.sync 1, 128;" ::: "memory");
  else asm volatile("bar.sync 2, 128;" ::: "memory");
}
template <int R> __device__ __forceinline__ void reg_alloc() { asm volatile("setmaxnreg.inc.sync.aligned.u32 %0;" ::"n"(R)); }
template <int R> __device__ __forceinline__ void reg_dealloc() { asm volatile("setmaxnreg.dec.sync.aligned.u32 %0;" ::"n"(R)); }

__device__ __forceinline__ uint64_t make_desc(uint32_t saddr, uint32_t lbo_bytes, uint32_t sbo_bytes, uint32_t layout) {
  uint64_t d = (uint64_t)((saddr & 0x3FFFF) >> 4);
  d |= (uint64_t)((lbo_bytes & 0x3FFFF) >> 4) << 16;
  d |= (uint64_t)((sbo_bytes & 0x3FFFF) >> 4) << 32;
  d |= (uint64_t)layout << 62;
  return d;
}
__device__ __forceinline__ uint64_t desc128(uint32_t lo) { return ((uint64_t)0x40000040u << 32) | lo; }
__device__ __forceinline__ uint32_t pack_bf16(float lo, float hi) {
  uint32_t r;
  asm("cvt.rn.bf16x2.f32 %0, %1, %2;" : "=r"(r) : "f"(hi), "f"(lo));
  return r;
}
__device__ __forceinline__ float ex2(float x) { float y; asm("ex2.approx.ftz.f32 %0, %1;" : "=f"(y) : "f"(x)); return y; }
__device__ __forceinline__ float rcp(float x) { float y; asm("rcp.approx.ftz.f32 %0, %1;" : "=f"(y) : "f"(x)); return y; }
__device__ __forceinline__ void stmatrix_x4(uint32_t addr, uint32_t r0, uint32_t r1, uint32_t r2, uint32_t r3) {
  asm volatile("stmatrix.sync.aligned.m8n8.x4.shared.b16 [%0], {%1, %2, %3, %4};" ::"r"(addr), "r"(r0), "r"(r1), "r"(r2), "r"(r3) : "memory");
}
template <int N> __device__ __forceinline__ void fence_regs(float (&d)[N]) {
#pragma unroll
  for (int i = 0; i < N; i++) asm volatile("" : "+f"(d[i])::"memory");
}

template <int TA, int TB>
__device__ __forceinline__ void wgmma_m64n128k16_ss(float (&d)[64], uint64_t descA, uint64_t descB) {
  asm volatile("{\n.reg .pred p;\nsetp.ne.b32 p, 1, 0;\n"
    "wgmma.mma_async.sync.aligned.m64n128k16.f32.bf16.bf16 "
    "{%0, %1, %2, %3, %4, %5, %6, %7, %8, %9, %10, %11, %12, %13, %14, %15, %16, %17, %18, %19, %20, %21, %22, %23, %24, %25, %26, %27, %28, %29, %30, %31, %32, %33, %34, %35, %36, %37, %38, %39, %40, %41, %42, %43, %44, %45, %46, %47, %48, %49, %50, %51, %52, %53, %54, %55, %56, %57, %58, %59, %60, %61, %62, %63}, "
    "%64, %65, p, 1, 1, %66, %67;\n}\n"
    : "+f"(d[0]), "+f"(d[1]), "+f"(d[2]), "+f"(d[3]), "+f"(d[4]), "+f"(d[5]), "+f"(d[6]), "+f"(d[7]), "+f"(d[8]), "+f"(d[9]), "+f"(d[10]), "+f"(d[11]), "+f"(d[12]), "+f"(d[13]), "+f"(d[14]), "+f"(d[15]), "+f"(d[16]), "+f"(d[17]), "+f"(d[18]), "+f"(d[19]), "+f"(d[20]), "+f"(d[21]), "+f"(d[22]), "+f"(d[23]), "+f"(d[24]), "+f"(d[25]), "+f"(d[26]), "+f"(d[27]), "+f"(d[28]), "+f"(d[29]), "+f"(d[30]), "+f"(d[31]), "+f"(d[32]), "+f"(d[33]), "+f"(d[34]), "+f"(d[35]), "+f"(d[36]), "+f"(d[37]), "+f"(d[38]), "+f"(d[39]), "+f"(d[40]), "+f"(d[41]), "+f"(d[42]), "+f"(d[43]), "+f"(d[44]), "+f"(d[45]), "+f"(d[46]), "+f"(d[47]), "+f"(d[48]), "+f"(d[49]), "+f"(d[50]), "+f"(d[51]), "+f"(d[52]), "+f"(d[53]), "+f"(d[54]), "+f"(d[55]), "+f"(d[56]), "+f"(d[57]), "+f"(d[58]), "+f"(d[59]), "+f"(d[60]), "+f"(d[61]), "+f"(d[62]), "+f"(d[63])
    : "l"(descA), "l"(descB), "n"(TA), "n"(TB));
}

template <int TA, int TB>
__device__ __forceinline__ void wgmma_m64n32k16_ss(float (&d)[16], uint64_t descA, uint64_t descB) {
  asm volatile("{\n.reg .pred p;\nsetp.ne.b32 p, 1, 0;\n"
    "wgmma.mma_async.sync.aligned.m64n32k16.f32.bf16.bf16 "
    "{%0, %1, %2, %3, %4, %5, %6, %7, %8, %9, %10, %11, %12, %13, %14, %15}, "
    "%16, %17, p, 1, 1, %18, %19;\n}\n"
    : "+f"(d[0]), "+f"(d[1]), "+f"(d[2]), "+f"(d[3]), "+f"(d[4]), "+f"(d[5]), "+f"(d[6]), "+f"(d[7]), "+f"(d[8]), "+f"(d[9]), "+f"(d[10]), "+f"(d[11]), "+f"(d[12]), "+f"(d[13]), "+f"(d[14]), "+f"(d[15])
    : "l"(descA), "l"(descB), "n"(TA), "n"(TB));
}

template <int TA, int TB>
__device__ __forceinline__ void wgmma_m64n32k16_ss_init(float (&d)[16], uint64_t descA, uint64_t descB) {
  asm volatile("{\n.reg .pred p;\nsetp.ne.b32 p, 0, 0;\n"
    "wgmma.mma_async.sync.aligned.m64n32k16.f32.bf16.bf16 "
    "{%0, %1, %2, %3, %4, %5, %6, %7, %8, %9, %10, %11, %12, %13, %14, %15}, "
    "%16, %17, p, 1, 1, %18, %19;\n}\n"
    : "=f"(d[0]), "=f"(d[1]), "=f"(d[2]), "=f"(d[3]), "=f"(d[4]), "=f"(d[5]), "=f"(d[6]), "=f"(d[7]), "=f"(d[8]), "=f"(d[9]), "=f"(d[10]), "=f"(d[11]), "=f"(d[12]), "=f"(d[13]), "=f"(d[14]), "=f"(d[15])
    : "l"(descA), "l"(descB), "n"(TA), "n"(TB));
}

template <int TA, int TB>
__device__ __forceinline__ void wgmma_m64n40k16_ss(float (&d)[20], uint64_t descA, uint64_t descB) {
  asm volatile("{\n.reg .pred p;\nsetp.ne.b32 p, 1, 0;\n"
    "wgmma.mma_async.sync.aligned.m64n40k16.f32.bf16.bf16 "
    "{%0, %1, %2, %3, %4, %5, %6, %7, %8, %9, %10, %11, %12, %13, %14, %15, %16, %17, %18, %19}, "
    "%20, %21, p, 1, 1, %22, %23;\n}\n"
    : "+f"(d[0]), "+f"(d[1]), "+f"(d[2]), "+f"(d[3]), "+f"(d[4]), "+f"(d[5]), "+f"(d[6]), "+f"(d[7]), "+f"(d[8]), "+f"(d[9]), "+f"(d[10]), "+f"(d[11]), "+f"(d[12]), "+f"(d[13]), "+f"(d[14]), "+f"(d[15]), "+f"(d[16]), "+f"(d[17]), "+f"(d[18]), "+f"(d[19])
    : "l"(descA), "l"(descB), "n"(TA), "n"(TB));
}

template <int TA, int TB>
__device__ __forceinline__ void wgmma_m64n40k16_ss_init(float (&d)[20], uint64_t descA, uint64_t descB) {
  asm volatile("{\n.reg .pred p;\nsetp.ne.b32 p, 0, 0;\n"
    "wgmma.mma_async.sync.aligned.m64n40k16.f32.bf16.bf16 "
    "{%0, %1, %2, %3, %4, %5, %6, %7, %8, %9, %10, %11, %12, %13, %14, %15, %16, %17, %18, %19}, "
    "%20, %21, p, 1, 1, %22, %23;\n}\n"
    : "=f"(d[0]), "=f"(d[1]), "=f"(d[2]), "=f"(d[3]), "=f"(d[4]), "=f"(d[5]), "=f"(d[6]), "=f"(d[7]), "=f"(d[8]), "=f"(d[9]), "=f"(d[10]), "=f"(d[11]), "=f"(d[12]), "=f"(d[13]), "=f"(d[14]), "=f"(d[15]), "=f"(d[16]), "=f"(d[17]), "=f"(d[18]), "=f"(d[19])
    : "l"(descA), "l"(descB), "n"(TA), "n"(TB));
}

template <int TB>
__device__ __forceinline__ void wgmma_m64n40k16_rs(float (&d)[20], uint32_t a0, uint32_t a1, uint32_t a2, uint32_t a3, uint64_t descB) {
  asm volatile("{\n.reg .pred p;\nsetp.ne.b32 p, 1, 0;\n"
    "wgmma.mma_async.sync.aligned.m64n40k16.f32.bf16.bf16 "
    "{%0, %1, %2, %3, %4, %5, %6, %7, %8, %9, %10, %11, %12, %13, %14, %15, %16, %17, %18, %19}, "
    "{%20, %21, %22, %23}, %24, p, 1, 1, %25;\n}\n"
    : "+f"(d[0]), "+f"(d[1]), "+f"(d[2]), "+f"(d[3]), "+f"(d[4]), "+f"(d[5]), "+f"(d[6]), "+f"(d[7]), "+f"(d[8]), "+f"(d[9]), "+f"(d[10]), "+f"(d[11]), "+f"(d[12]), "+f"(d[13]), "+f"(d[14]), "+f"(d[15]), "+f"(d[16]), "+f"(d[17]), "+f"(d[18]), "+f"(d[19])
    : "r"(a0), "r"(a1), "r"(a2), "r"(a3), "l"(descB), "n"(TB));
}

template <int TB>
__device__ __forceinline__ void wgmma_m64n40k16_rs_init(float (&d)[20], uint32_t a0, uint32_t a1, uint32_t a2, uint32_t a3, uint64_t descB) {
  asm volatile("{\n.reg .pred p;\nsetp.ne.b32 p, 0, 0;\n"
    "wgmma.mma_async.sync.aligned.m64n40k16.f32.bf16.bf16 "
    "{%0, %1, %2, %3, %4, %5, %6, %7, %8, %9, %10, %11, %12, %13, %14, %15, %16, %17, %18, %19}, "
    "{%20, %21, %22, %23}, %24, p, 1, 1, %25;\n}\n"
    : "=f"(d[0]), "=f"(d[1]), "=f"(d[2]), "=f"(d[3]), "=f"(d[4]), "=f"(d[5]), "=f"(d[6]), "=f"(d[7]), "=f"(d[8]), "=f"(d[9]), "=f"(d[10]), "=f"(d[11]), "=f"(d[12]), "=f"(d[13]), "=f"(d[14]), "=f"(d[15]), "=f"(d[16]), "=f"(d[17]), "=f"(d[18]), "=f"(d[19])
    : "r"(a0), "r"(a1), "r"(a2), "r"(a3), "l"(descB), "n"(TB));
}

template <int MODE>
__device__ __forceinline__ void mainloop(float (&acc0)[64], float (&acc1)[64], int it0, int nkb, uint32_t sbase, int cw,
                                         uint32_t ord_parity) {
  const uint32_t bars = sbase + OFF_BAR;
  const int lane = threadIdx.x & 31;
  int stage = it0 % STAGES;
  uint32_t phase = (it0 / STAGES) & 1;
#pragma unroll
  for (int i = 0; i < 64; i++) { acc0[i] = 0.f; acc1[i] = 0.f; }
  mbar_wait(bars + B_ORD + 8 * cw, ord_parity);
  int prev = 0;
  for (int kb = 0; kb < nkb; kb++) {
    mbar_wait(bars + 8 * stage, phase);
    if (kb == nkb - 1 && (threadIdx.x & 127) == 0) mbar_arrive(bars + B_ORD + 8 * (cw ^ 1));
    const uint32_t lo = ((sbase & 0x3FFFFu) + stage * STAGE_BYTES) >> 4;
    const uint32_t loK = lo | (1u << 16), loM = lo | (512u << 16);
    wgmma_fence();
#pragma unroll
    for (int k = 0; k < 4; k++) {
      if (MODE == 0) {
        const uint64_t dx = desc128(loK + 1024 + 2 * k);
        wgmma_m64n128k16_ss<0, 0>(acc0, desc128(loK + 2 * k), dx);
        wgmma_m64n128k16_ss<0, 0>(acc1, desc128(loK + 512 + 2 * k), dx);
      } else if (MODE == 1) {
        const uint64_t dw = desc128(loM + 128 * k);
        wgmma_m64n128k16_ss<0, 1>(acc0, desc128(loK + 1024 + 2 * k), dw);
        wgmma_m64n128k16_ss<0, 1>(acc1, desc128(loK + 1536 + 2 * k), dw);
      } else {
        const uint64_t dw = desc128(loK + 2 * k);
        wgmma_m64n128k16_ss<1, 0>(acc0, desc128(loM + 1024 + 128 * k), dw);
        wgmma_m64n128k16_ss<1, 0>(acc1, desc128(loM + 1536 + 128 * k), dw);
      }
    }
    wgmma_commit();
    wgmma_wait<1>();
    if (kb > 0 && lane < 2) mbar_arrive_cluster(bars + B_EMPTY + 8 * prev, lane);
    prev = stage;
    if (++stage == STAGES) { stage = 0; phase ^= 1; }
  }
  wgmma_wait<0>();
  if (lane < 2) mbar_arrive_cluster(bars + B_EMPTY + 8 * prev, lane);
  fence_regs(acc0);
  fence_regs(acc1);
}

template <int N>
__device__ __forceinline__ void dual_softmax_n(const float (&p)[N][16], uint32_t (&pos)[N][8], uint32_t (&neg)[N][8]) {
  constexpr float L2E = 1.4426950408889634f;
  float ca[N][2], cb[N][2];
  {
    float mx[N][2], mn[N][2];
#pragma unroll
    for (int i = 0; i < N; i++)
#pragma unroll
      for (int r = 0; r < 2; r++) {
        const int o = 2 * r;
        mx[i][r] = fmaxf(fmaxf(fmaxf(p[i][o], p[i][o + 1]), fmaxf(p[i][4 + o], p[i][5 + o])),
                         fmaxf(fmaxf(p[i][8 + o], p[i][9 + o]), fmaxf(p[i][12 + o], p[i][13 + o])));
        mn[i][r] = fminf(fminf(fminf(p[i][o], p[i][o + 1]), fminf(p[i][4 + o], p[i][5 + o])),
                         fminf(fminf(p[i][8 + o], p[i][9 + o]), fminf(p[i][12 + o], p[i][13 + o])));
      }
#pragma unroll
    for (int o = 1; o <= 2; o <<= 1) {
      float tx[N][2], tn[N][2];
#pragma unroll
      for (int i = 0; i < N; i++)
#pragma unroll
        for (int r = 0; r < 2; r++) { tx[i][r] = __shfl_xor_sync(0xffffffffu, mx[i][r], o); tn[i][r] = __shfl_xor_sync(0xffffffffu, mn[i][r], o); }
#pragma unroll
      for (int i = 0; i < N; i++)
#pragma unroll
        for (int r = 0; r < 2; r++) { mx[i][r] = fmaxf(mx[i][r], tx[i][r]); mn[i][r] = fminf(mn[i][r], tn[i][r]); }
    }
#pragma unroll
    for (int i = 0; i < N; i++)
#pragma unroll
      for (int r = 0; r < 2; r++) { ca[i][r] = -mx[i][r] * L2E; cb[i][r] = mn[i][r] * L2E; }
  }
  float ep[2][16], en[2][16];
  float rp[2], rn[2];
#pragma unroll
  for (int i = 0; i <= N; i++) {
    const int cur = i & 1, prv = cur ^ 1;
    if (i > 0) {
      float sp[2], sn[2];
#pragma unroll
      for (int r = 0; r < 2; r++) {
        const int o = 2 * r;
        sp[r] = ((ep[prv][o] + ep[prv][o + 1]) + (ep[prv][4 + o] + ep[prv][5 + o])) + ((ep[prv][8 + o] + ep[prv][9 + o]) + (ep[prv][12 + o] + ep[prv][13 + o]));
        sn[r] = ((en[prv][o] + en[prv][o + 1]) + (en[prv][4 + o] + en[prv][5 + o])) + ((en[prv][8 + o] + en[prv][9 + o]) + (en[prv][12 + o] + en[prv][13 + o]));
      }
      float t0[2], t1[2];
#pragma unroll
      for (int r = 0; r < 2; r++) { t0[r] = __shfl_xor_sync(0xffffffffu, sp[r], 1); t1[r] = __shfl_xor_sync(0xffffffffu, sn[r], 1); }
      if (i < N) {
#pragma unroll
        for (int e = 0; e < 4; e++) {
          ep[cur][e] = ex2(fmaf(p[i][e], L2E, ca[i][e >> 1])); en[cur][e] = ex2(fmaf(p[i][e], -L2E, cb[i][e >> 1]));
        }
      }
#pragma unroll
      for (int r = 0; r < 2; r++) { sp[r] += t0[r]; sn[r] += t1[r]; }
#pragma unroll
      for (int r = 0; r < 2; r++) { t0[r] = __shfl_xor_sync(0xffffffffu, sp[r], 2); t1[r] = __shfl_xor_sync(0xffffffffu, sn[r], 2); }
      if (i < N) {
#pragma unroll
        for (int e = 4; e < 8; e++) {
          ep[cur][e] = ex2(fmaf(p[i][e], L2E, ca[i][(e >> 1) & 1])); en[cur][e] = ex2(fmaf(p[i][e], -L2E, cb[i][(e >> 1) & 1]));
        }
      }
#pragma unroll
      for (int r = 0; r < 2; r++) { rp[r] = rcp(sp[r] + t0[r]); rn[r] = rcp(sn[r] + t1[r]); }
    } else {
#pragma unroll
      for (int e = 0; e < 8; e++) {
        ep[cur][e] = ex2(fmaf(p[i][e], L2E, ca[i][(e >> 1) & 1])); en[cur][e] = ex2(fmaf(p[i][e], -L2E, cb[i][(e >> 1) & 1]));
      }
    }
#pragma unroll
    for (int j = 0; j < 4; j++) {
      if (i < N && j >= 2) {
#pragma unroll
        for (int e = 4 * j; e < 4 * j + 4; e++) {
          ep[cur][e] = ex2(fmaf(p[i][e], L2E, ca[i][(e >> 1) & 1])); en[cur][e] = ex2(fmaf(p[i][e], -L2E, cb[i][(e >> 1) & 1]));
        }
      }
      if (i > 0) {
#pragma unroll
        for (int r = 0; r < 2; r++) {
          pos[i - 1][2 * j + r] = pack_bf16(ep[prv][4 * j + 2 * r] * rp[r], ep[prv][4 * j + 2 * r + 1] * rp[r]);
          neg[i - 1][2 * j + r] = pack_bf16(en[prv][4 * j + 2 * r] * rn[r], en[prv][4 * j + 2 * r + 1] * rn[r]);
        }
      }
    }
  }
}

struct cplx { float r, i; };
__device__ __forceinline__ cplx cmul(cplx a, cplx b) { return {a.r * b.r - a.i * b.i, a.r * b.i + a.i * b.r}; }
__device__ __forceinline__ cplx cfma(cplx a, cplx b, cplx c) {
  return {fmaf(a.r, b.r, fmaf(-a.i, b.i, c.r)), fmaf(a.r, b.i, fmaf(a.i, b.r, c.i))};
}
__device__ __forceinline__ cplx shfl_up_c(cplx v, int d) {
  return {__shfl_up_sync(0xffffffffu, v.r, d, 4), __shfl_up_sync(0xffffffffu, v.i, d, 4)};
}

struct ChanParams { cplx lam, c2; };

__device__ __forceinline__ ChanParams chan_params(float lr, float li, float log_dt) {
  const float dt = __bfloat162float(__float2bfloat16(expf(log_dt)));
  const float mag = expf(dt * lr);
  float sn, cs;
  sincosf(dt * li, &sn, &cs);
  ChanParams c;
  c.lam = {mag * cs, mag * sn};
  const float nr = c.lam.r - 1.0f, ni = c.lam.i;
  const float den = lr * lr + li * li;
  c.c2 = {2.0f * (nr * lr + ni * li) / den, 2.0f * (ni * lr - nr * li) / den};
  return c;
}

__device__ __forceinline__ void epi_bu(float (&are)[64], float (&aim)[64], const ChanParams (&cp)[2],
                                       uint32_t sbase, int G, int chunk, int cw, unsigned epoch) {
  const int lane = threadIdx.x & 31, w = (threadIdx.x & 127) >> 5, q = lane & 3, r8 = lane >> 2;
  cplx E[2] = {{0.f, 0.f}, {0.f, 0.f}};
#pragma unroll
  for (int k8 = 0; k8 < 16; k8++)
#pragma unroll
    for (int e = 0; e < 2; e++)
#pragma unroll
      for (int c = 0; c < 2; c++) E[c] = cfma(cp[c].lam, E[c], cplx{are[4 * k8 + 2 * c + e], aim[4 * k8 + 2 * c + e]});
  TSTAMP(32 + 4 * (threadIdx.x >> 8));
  cplx L32[2], L128[2], prev[2];
#pragma unroll
  for (int c = 0; c < 2; c++) {
    cplx l = cp[c].lam;
#pragma unroll
    for (int s = 0; s < 5; s++) l = cmul(l, l);
    L32[c] = l;
    const cplx l64 = cmul(l, l);
    L128[c] = cmul(l64, l64);
    cplx t = shfl_up_c(E[c], 1);
    if (q >= 1) E[c] = cfma(L32[c], t, E[c]);
    t = shfl_up_c(E[c], 2);
    if (q >= 2) E[c] = cfma(l64, t, E[c]);
    prev[c] = shfl_up_c(E[c], 1);
    if (q == 0) prev[c] = {0.f, 0.f};
  }
  uint4* gE = g_E + (size_t)G * 16 * 64 + 16 * w + r8;
  if (q == 3) {
    st_tagged(gE + chunk * 64, E[0].r, E[0].i, epoch);
    st_tagged(gE + chunk * 64 + 8, E[1].r, E[1].i, epoch);
  }
  cplx V[2][4];
  {
    unsigned long long w0[8], w1[8];
    unsigned pending = 0;
#pragma unroll
    for (int i = 0; i < 8; i++) {
      w0[i] = 0ull; w1[i] = 0ull;
      if (chunk - 1 - 4 * q - (i & 3) >= 0) pending |= 1u << i;
    }
    unsigned spins = 0;
    if (chunk > 0) __nanosleep(300);
    while (true) {
#pragma unroll
      for (int i = 0; i < 8; i++)
        asm volatile("{\n.reg .pred p;\nsetp.ne.u32 p, %3, 0;\n@p ld.relaxed.gpu.global.v2.b64 {%0, %1}, [%2];\n}"
                     : "+l"(w0[i]), "+l"(w1[i]) : "l"(gE + (chunk - 1 - 4 * q - (i & 3)) * 64 + 8 * (i >> 2)), "r"(pending & (1u << i)) : "memory");
#pragma unroll
      for (int i = 0; i < 8; i++)
        if ((unsigned)(w0[i] >> 32) == epoch && (unsigned)(w1[i] >> 32) == epoch) pending &= ~(1u << i);
      if (__all_sync(0xffffffffu, pending == 0)) break;
      __nanosleep(150);
      if (give_up(sbase + OFF_BAR, ++spins)) break;
    }
#pragma unroll
    for (int i = 0; i < 8; i++) V[i >> 2][i & 3] = {__uint_as_float((unsigned)w0[i]), __uint_as_float((unsigned)w1[i])};
  }
  TSTAMP(33 + 4 * (threadIdx.x >> 8));
  cplx s[2];
#pragma unroll
  for (int c = 0; c < 2; c++) {
    cplx Pq = V[c][3];
#pragma unroll
    for (int jj = 2; jj >= 0; jj--) Pq = cfma(L128[c], Pq, V[c][jj]);
    const cplx l256 = cmul(L128[c], L128[c]);
    const cplx l512 = cmul(l256, l256);
    cplx F = {1.f, 0.f};
    cplx G32 = {1.f, 0.f};
    if (q >= 1) { F = l512; G32 = L32[c]; }
    if (q >= 2) { F = cmul(F, l512); G32 = cmul(G32, L32[c]); }
    if (q >= 3) { F = cmul(F, l512); G32 = cmul(G32, L32[c]); }
    Pq = cmul(Pq, F);
#pragma unroll
    for (int o = 1; o <= 2; o <<= 1) {
      Pq.r += __shfl_xor_sync(0xffffffffu, Pq.r, o);
      Pq.i += __shfl_xor_sync(0xffffffffu, Pq.i, o);
    }
    s[c] = cfma(G32, Pq, prev[c]);
  }
  TSTAMP(34 + 4 * (threadIdx.x >> 8));
  if (cw == 1) mbar_wait(sbase + OFF_BAR + B_EBF, 0);
#pragma unroll
  for (int qq = 0; qq < 4; qq++) {
    uint32_t ore[2][4], oim[2][4];
#pragma unroll
    for (int kk = 0; kk < 4; kk++) {
      const int k8 = 4 * qq + kk;
      float hr[2][2], hi[2][2];
#pragma unroll
      for (int e = 0; e < 2; e++)
#pragma unroll
        for (int c = 0; c < 2; c++) {
          s[c] = cfma(cp[c].lam, s[c], cplx{are[4 * k8 + 2 * c + e], aim[4 * k8 + 2 * c + e]});
          hr[c][e] = fmaf(cp[c].c2.r, s[c].r, -cp[c].c2.i * s[c].i);
          hi[c][e] = -fmaf(cp[c].c2.r, s[c].i, cp[c].c2.i * s[c].r);
        }
#pragma unroll
      for (int c = 0; c < 2; c++) {
        ore[c][kk] = pack_bf16(hr[c][0], hr[c][1]);
        oim[c][kk] = pack_bf16(hi[c][0], hi[c][1]);
      }
    }
#pragma unroll
    for (int c = 0; c < 2; c++) {
      const int row = 16 * w + r8 + 8 * c;
      const uint32_t addr = sbase + OFF_PHI + (qq >> 1) * 8192 + row * 128 + ((((qq & 1) * 4 + q) ^ (row & 7)) << 4);
      asm volatile("st.shared.v4.b32 [%0], {%1, %2, %3, %4};" ::"r"(addr), "r"(ore[c][0]), "r"(ore[c][1]), "r"(ore[c][2]), "r"(ore[c][3]) : "memory");
      asm volatile("st.shared.v4.b32 [%0], {%1, %2, %3, %4};" ::"r"(addr + 16384), "r"(oim[c][0]), "r"(oim[c][1]), "r"(oim[c][2]), "r"(oim[c][3]) : "memory");
    }
  }
  TSTAMP(35 + 4 * (threadIdx.x >> 8));
  fence_async_smem();
  wg_bar(1 + cw);
  if ((threadIdx.x & 127) == 0) mbar_arrive(sbase + OFF_BAR + B_JOB + 8 * cw);
}

__device__ __forceinline__ void q_issue_num(float (&num)[20], const uint32_t (&pos)[8], const uint32_t (&neg)[8], uint32_t b) {
  wgmma_fence();
  wgmma_m64n40k16_rs_init<1>(num, pos[0], pos[1], pos[2], pos[3], make_desc(b, 640, 128, 0));
  wgmma_m64n40k16_rs<1>(num, pos[4], pos[5], pos[6], pos[7], make_desc(b + 1280, 640, 128, 0));
  wgmma_m64n40k16_rs<1>(num, neg[0], neg[1], neg[2], neg[3], make_desc(b + 2560, 640, 128, 0));
  wgmma_m64n40k16_rs<1>(num, neg[4], neg[5], neg[6], neg[7], make_desc(b + 3840, 640, 128, 0));
  wgmma_commit();
}
__device__ __forceinline__ void q_store_o(const float (&num)[20], uint32_t rowaddr, int chunk0) {
  const int lane = threadIdx.x & 31, mi = lane >> 3, rin = lane & 7;
  const float d0 = __shfl_sync(0xffffffffu, num[16], lane & ~3), d1 = __shfl_sync(0xffffffffu, num[18], lane & ~3);
  const float i0 = __fdividef(1.0f, d0 + 1e-6f), i1 = __fdividef(1.0f, d1 + 1e-6f);
#pragma unroll
  for (int jp = 0; jp < 2; jp++) {
    const int c0 = chunk0 + jp * 2 + (mi >> 1);
    stmatrix_x4(rowaddr + ((c0 ^ rin) << 4), pack_bf16(num[8 * jp] * i0, num[8 * jp + 1] * i0),
                pack_bf16(num[8 * jp + 2] * i1, num[8 * jp + 3] * i1), pack_bf16(num[8 * jp + 4] * i0, num[8 * jp + 5] * i0),
                pack_bf16(num[8 * jp + 6] * i1, num[8 * jp + 7] * i1));
  }
}
__device__ __forceinline__ void epi_attn(float (&acc0)[64], float (&acc1)[64], uint32_t sbase, int cw, bool isq) {
  const int t = threadIdx.x & 127, lane = t & 31, w = t >> 5, q = lane & 3, r8 = lane >> 2;
  const int mi = lane >> 3, rin = lane & 7;
  const int row0 = w * 16 + (mi & 1) * 8 + rin;
  {
    const uint32_t tile = sbase + OFF_PHI + (isq ? 0 : 16384) + row0 * 128;
#pragma unroll
    for (int j = 0; j < 8; j += 2) {
      const uint32_t addr = tile + (((j + (mi >> 1)) ^ rin) << 4);
      stmatrix_x4(addr, pack_bf16(acc0[4 * j], acc0[4 * j + 1]), pack_bf16(acc0[4 * j + 2], acc0[4 * j + 3]),
                  pack_bf16(acc0[4 * j + 4], acc0[4 * j + 5]), pack_bf16(acc0[4 * j + 6], acc0[4 * j + 7]));
      stmatrix_x4(addr + 8192, pack_bf16(acc1[4 * j], acc1[4 * j + 1]), pack_bf16(acc1[4 * j + 2], acc1[4 * j + 3]),
                  pack_bf16(acc1[4 * j + 4], acc1[4 * j + 5]), pack_bf16(acc1[4 * j + 6], acc1[4 * j + 7]));
    }
  }
#pragma unroll
  for (int j = 8; j < 16; j += 2) {
    const uint32_t aq = sbase + OFF_PHI + 16384 + row0 * 128 + (((j - 8 + (mi >> 1)) ^ rin) << 4);
    const uint32_t av = sbase + OFF_V + ((j - 8) >> 2) * 8192 + row0 * 64 + ((((j & 3) + (mi >> 1)) ^ ((row0 >> 1) & 3)) << 4);
    const uint32_t addr = isq ? aq : av;
    stmatrix_x4(addr, pack_bf16(acc0[4 * j], acc0[4 * j + 1]), pack_bf16(acc0[4 * j + 2], acc0[4 * j + 3]),
                pack_bf16(acc0[4 * j + 4], acc0[4 * j + 5]), pack_bf16(acc0[4 * j + 6], acc0[4 * j + 7]));
    stmatrix_x4(addr + (isq ? 8192 : 4096), pack_bf16(acc1[4 * j], acc1[4 * j + 1]), pack_bf16(acc1[4 * j + 2], acc1[4 * j + 3]),
                pack_bf16(acc1[4 * j + 4], acc1[4 * j + 5]), pack_bf16(acc1[4 * j + 6], acc1[4 * j + 7]));
  }
  fence_async_smem();
  wg_bar(1 + cw);
  TSTAMP(isq ? 56 : 40 + 8 * cw);
  const int nsub = isq ? 2 : 1;
#pragma unroll 1
  for (int sub = 0; sub < nsub; sub++) {
    const int it = 4 * sub;
    (void)it;
    const uint32_t tile = sbase + OFF_PHI + (isq ? sub : 1) * 16384;
    const uint32_t wp = sbase + OFF_WPHI + (isq ? 2 * sub : 2 * cw) * 2048;
    float pq[4][16];
    uint32_t pos[4][8], neg[4][8];
    QT(0);
    wgmma_fence();
#pragma unroll
    for (int i = 0; i < 4; i++) {
      const uint32_t a = tile + (i & 1) * 8192 + (i >> 1) * 64, b = wp + (i >> 1) * 2048;
      wgmma_m64n32k16_ss_init<0, 1>(pq[i], make_desc(a, 16, 1024, 1), make_desc(b, 512, 512, 2));
      wgmma_m64n32k16_ss<0, 1>(pq[i], make_desc(a + 32, 16, 1024, 1), make_desc(b + 1024, 512, 512, 2));
    }
    wgmma_commit();
    wgmma_wait<0>();
#pragma unroll
    for (int i = 0; i < 4; i++) fence_regs(pq[i]);
    QT(1);
    dual_softmax_n<4>(pq, pos, neg);
    QT(2);
    if (!isq) {
      float kvacc[2][20];
#pragma unroll
      for (int hh = 0; hh < 2; hh++) {
#pragma unroll
        for (int half = 0; half < 2; half++) {
          const uint32_t rb = sbase + OFF_PHI + hh * 16384 + (half * 64 + row0) * 128;
#pragma unroll
          for (int jp = 0; jp < 2; jp++) {
            const int c0 = jp * 2 + (mi >> 1), i = 2 * hh + half;
            stmatrix_x4(rb + ((c0 ^ rin) << 4), pos[i][4 * jp], pos[i][4 * jp + 1], pos[i][4 * jp + 2], pos[i][4 * jp + 3]);
            stmatrix_x4(rb + (((c0 + 4) ^ rin) << 4), neg[i][4 * jp], neg[i][4 * jp + 1], neg[i][4 * jp + 2], neg[i][4 * jp + 3]);
          }
        }
      }
      fence_async_smem();
      wg_bar(1 + cw);
      wgmma_fence();
#pragma unroll
      for (int hh = 0; hh < 2; hh++)
#pragma unroll
        for (int ks = 0; ks < 8; ks++) {
          const uint32_t vb = sbase + OFF_V + hh * 8192 + ks * 1024;
          const uint64_t da = make_desc(sbase + OFF_PHI + hh * 16384 + ks * 2048, 1024, 1024, 1);
          const uint64_t db = make_desc(vb, sbase + OFF_ONES - vb, 512, 2);
          if (ks == 0) wgmma_m64n40k16_ss_init<1, 1>(kvacc[hh], da, db);
          else wgmma_m64n40k16_ss<1, 1>(kvacc[hh], da, db);
        }
      wgmma_commit();
      TSTAMP(42 + 8 * cw);
      wgmma_wait<0>();
      fence_regs(kvacc[0]);
      fence_regs(kvacc[1]);
      TSTAMP(43 + 8 * cw);
      wg_bar(1 + cw);
#pragma unroll
      for (int hh = 0; hh < 2; hh++) {
        const uint32_t dst = sbase + OFF_PHI + hh * 16384 + ((16 * w + r8) * KVW + 2 * q) * 4;
#pragma unroll
        for (int j = 0; j < 5; j++) {
          asm volatile("st.shared.v2.f32 [%0], {%1, %2};" ::"r"(dst + 32 * j), "f"(kvacc[hh][4 * j]), "f"(kvacc[hh][4 * j + 1]) : "memory");
          asm volatile("st.shared.v2.f32 [%0], {%1, %2};" ::"r"(dst + 8 * KVW * 4 + 32 * j), "f"(kvacc[hh][4 * j + 2]), "f"(kvacc[hh][4 * j + 3]) : "memory");
        }
      }
      fence_async_smem();
      wg_bar(1 + cw);
      if (t == 0) mbar_arrive(sbase + OFF_BAR + B_JOB + 16 + 8 * cw);
      TSTAMP(44 + 8 * cw);
    } else {
      float num[4][20];
      mbar_wait(sbase + OFF_BAR + B_KVX + 8 * sub, 0);
      TSTAMP(57 + sub);
      QT(3);
#pragma unroll
      for (int i = 0; i < 4; i++) q_issue_num(num[i], pos[i], neg[i], sbase + OFF_V + (2 * sub + (i >> 1)) * 5120);
      QT(4);
      wgmma_wait<2>();
      fence_regs(num[0]); fence_regs(num[1]);
      QT(5);
      q_store_o(num[0], tile + row0 * 128, 0);
      q_store_o(num[1], tile + 8192 + row0 * 128, 0);
      wgmma_wait<0>();
      fence_regs(num[2]); fence_regs(num[3]);
      QT(6);
      q_store_o(num[2], tile + row0 * 128, 4);
      q_store_o(num[3], tile + 8192 + row0 * 128, 4);
      QT(7);
      fence_async_smem();
      wg_bar(1);
      if (t == 0) mbar_arrive(sbase + OFF_BAR + B_JOB + 32 + 8 * sub);
    }
  }
}

__device__ __forceinline__ void helper_kv(uint32_t sbase, int g, unsigned epoch) {
  const int h = threadIdx.x - 64;
  mbar_wait(sbase + OFF_BAR + B_E3, 0);
#pragma unroll 1
  for (int pr = 0; pr < 2; pr++) {
    if ((h & 31) == 0) wait_ge(sbase + OFF_BAR, &g_flags.kvcnt[(g + 8 * pr) * 8], 16u * epoch);
    __syncwarp();
    const float4* src = reinterpret_cast<const float4*>(g_kv + (size_t)(2 * g + 16 * pr) * 64 * KVW);
#pragma unroll 1
    for (int ib = 0; ib < 3; ib++) {
      float4 u[7];
#pragma unroll
      for (int i = 0; i < 7; i++) u[i] = __ldcg(src + min((ib * 7 + i) * 64 + h, 1279));
#pragma unroll
      for (int i = 0; i < 7; i++) {
        const int idx = min((ib * 7 + i) * 64 + h, 1279);
        const int f2 = idx / 10, j = idx - f2 * 10;
        const uint32_t dst = sbase + OFF_V + pr * 10240 + (f2 >> 3) * 640 + (j >> 1) * 128 + (f2 & 7) * 16 + (j & 1) * 8;
        asm volatile("st.shared.v2.b32 [%0], {%1, %2};" ::"r"(dst), "r"(pack_bf16(u[i].x, u[i].y)), "r"(pack_bf16(u[i].z, u[i].w)) : "memory");
      }
    }
    fence_async_smem();
    __syncwarp();
    if ((h & 31) == 0) mbar_arrive(sbase + OFF_BAR + B_KVX + 8 * pr);
  }
}

__device__ __forceinline__ void store_agent(const Params& prm, uint32_t sbase, int g, int rb, unsigned epoch) {
  const uint32_t bars = sbase + OFF_BAR;
#pragma unroll 1
  for (int j = 0; j < 6; j++) {
    mbar_wait(bars + B_JOB + 8 * j, 0);
    unsigned* flag;
    if (j < 2) {
      const int G = g + 8 * j;
      tma_store_3d(&prm.tmHT, sbase + OFF_PHI, 0, 64 * G, 2 * rb);
      tma_store_3d(&prm.tmHT, sbase + OFF_PHI + 16384, 0, 1024 + 64 * G, 2 * rb);
      flag = &g_flags.hcnt[rb * 8];
    } else if (j < 4) {
      const int hp = g + 8 * (j - 2);
      wait_ge(bars, &g_flags.zero_cnt, 128u * epoch);
      bulk_reduce_f32(g_kv + (size_t)(2 * hp) * 64 * KVW, sbase + OFF_PHI, 64 * KVW * 4);
      bulk_reduce_f32(g_kv + (size_t)(2 * hp + 1) * 64 * KVW, sbase + OFF_PHI + 16384, 64 * KVW * 4);
      flag = &g_flags.kvcnt[hp * 8];
    } else {
      tma_store_2d(&prm.tmO, sbase + OFF_PHI + (j - 4) * 16384, 64 * (g + 8 * (j - 4)), 128 * rb);
      flag = &g_flags.ocnt[(2 * rb + (j - 4)) * 8];
    }
    bulk_commit();
    if (j != 4) {
      bulk_wait_read();
      mbar_arrive(bars + B_EBF);
      if (j == 3) mbar_arrive(bars + B_E3);
    }
    bulk_wait_all();
    red_relaxed_add(flag, 1);
  }
}

constexpr int OST = 544;
__device__ __forceinline__ float bf16_round(float x) { return __bfloat162float(__float2bfloat16(x)); }
__device__ __forceinline__ void stage_half(const float (&a)[64], uint32_t wbuf) {
  const int lane = threadIdx.x & 31, q = lane & 3, r8 = lane >> 2;
#pragma unroll
  for (int j = 0; j < 16; j++) {
    asm volatile("st.shared.v2.f32 [%0], {%1, %2};" ::"r"(wbuf + r8 * OST + j * 32 + q * 8), "f"(a[4 * j]), "f"(a[4 * j + 1]) : "memory");
    asm volatile("st.shared.v2.f32 [%0], {%1, %2};" ::"r"(wbuf + (r8 + 8) * OST + j * 32 + q * 8), "f"(a[4 * j + 2]), "f"(a[4 * j + 3]) : "memory");
  }
  __syncwarp();
}
__device__ __forceinline__ float4 lds128(uint32_t addr) {
  float4 v;
  asm volatile("ld.shared.v4.f32 {%0, %1, %2, %3}, [%4];" : "=f"(v.x), "=f"(v.y), "=f"(v.z), "=f"(v.w) : "r"(addr) : "memory");
  return v;
}
template <bool IS_Y>
__device__ __forceinline__ void store_tile(float (&acc0)[64], const float (&acc1)[64], uint32_t wbuf, const Params& prm, int rb, int g) {
  const int lane = threadIdx.x & 31, w = (threadIdx.x & 127) >> 5;
  uint2 dk = make_uint2(0, 0);
  if (IS_Y) dk = __ldg(reinterpret_cast<const uint2*>(prm.dskip + 128 * g) + lane);
#pragma unroll 1
  for (int half = 0; half < 2; half++) {
    const int m0 = 64 * half + 16 * w;
    const int t0 = rb * 128 + (IS_Y ? 32 * ((m0 >> 3) & 3) + 8 * (m0 >> 5) : m0);
    uint2 xs[16];
    if (IS_Y) {
#pragma unroll
      for (int r = 0; r < 16; r++)
        xs[r] = __ldg(reinterpret_cast<const uint2*>(prm.xB + (size_t)(t0 + (r & 7) + (r >> 3) * 32) * DM + 128 * g) + lane);
    }
    stage_half(acc0, wbuf);
    float* dst = prm.out + (size_t)t0 * 2048 + (IS_Y ? 1024 : 0) + 128 * g + 4 * lane;
#pragma unroll
    for (int r = 0; r < 16; r++) {
      float4 v = lds128(wbuf + r * OST + lane * 16);
      if (IS_Y) {
        const float2 s0 = __bfloat1622float2(__hmul2(*reinterpret_cast<const __nv_bfloat162*>(&xs[r].x), *reinterpret_cast<const __nv_bfloat162*>(&dk.x)));
        const float2 s1 = __bfloat1622float2(__hmul2(*reinterpret_cast<const __nv_bfloat162*>(&xs[r].y), *reinterpret_cast<const __nv_bfloat162*>(&dk.y)));
        v.x += s0.x; v.y += s0.y; v.z += s1.x; v.w += s1.y;
      } else {
        v.x = bf16_round(v.x); v.y = bf16_round(v.y); v.z = bf16_round(v.z); v.w = bf16_round(v.w);
      }
      __stcs(reinterpret_cast<float4*>(dst + (size_t)((r & 7) + (r >> 3) * (IS_Y ? 32 : 8)) * 2048), v);
    }
    __syncwarp();
#pragma unroll
    for (int i = 0; i < 64; i++) acc0[i] = acc1[i];
  }
}

__global__ void __launch_bounds__(384, 1) fused_kernel(const __grid_constant__ Params prm) {
  extern __shared__ uint8_t smem_raw[];
  const uint32_t sbase = (smem_u32(smem_raw) + 1023) & ~1023u;
  const uint32_t bars = sbase + OFF_BAR;
  const int tid = threadIdx.x, wg = __shfl_sync(0xffffffffu, tid >> 7, 0);
  const int cl = blockIdx.x >> 1, rank = blockIdx.x & 1;
  const int g = cl >> 3, rb = 2 * (cl & 7) + rank;

  if (tid == 0) {
    for (int s = 0; s < STAGES; s++) { mbar_init(bars + 8 * s, 1);
      mbar_init(bars + B_EMPTY + 8 * s, 8);
    }
    mbar_init(bars + B_ORD, 1); mbar_init(bars + B_ORD + 8, 1); mbar_init(bars + B_EBF, 1); mbar_init(bars + B_WPHI, 1); mbar_init(bars + B_EPOCH, 1); mbar_init(bars + B_KVX, 2); mbar_init(bars + B_KVX + 8, 2);
    for (int j = 0; j < 6; j++) mbar_init(bars + B_JOB + 8 * j, 1);
    mbar_init(bars + B_PARAM, 2); mbar_init(bars + B_E3, 1);
    asm volatile("st.shared.u32 [%0], %1;" ::"r"(bars + B_DEAD), "r"(0u) : "memory");
    asm volatile("fence.mbarrier_init.release.cluster;" ::: "memory");
  } else if (tid == 32) {
    prefetch_tm(&prm.tmXB); prefetch_tm(rank ? &prm.tmBim : &prm.tmBre); prefetch_tm(&prm.tmWphi);
    prefetch_tm(&prm.tmXA); prefetch_tm(&prm.tmWqkv); prefetch_tm(&prm.tmHT);
    prefetch_tm(&prm.tmCre); prefetch_tm(&prm.tmCim); prefetch_tm(&prm.tmO); prefetch_tm(&prm.tmWo);
  } else if (tid >= 64 && tid < 128) {
    asm volatile("st.shared.v4.b32 [%0], {%1, %2, %2, %2};" ::"r"(sbase + OFF_ONES + (tid - 64) * 16), "r"(0x00003F80u), "r"(0u) : "memory");
    fence_async_smem();
  }
  __syncthreads();
  asm volatile("barrier.cluster.arrive.relaxed.aligned;\nbarrier.cluster.wait.acquire.aligned;" ::: "memory");

  if (wg == 0) {
    reg_dealloc<56>();
    const int warp = tid >> 5, lane = tid & 31;
    if (warp == 0) {
      if (lane == 0) {
        TSTAMP(0);
        mbar_expect_tx(bars + B_WPHI, 8192);
        tma_2d(sbase + OFF_WPHI, &prm.tmWphi, 0, 64 * g, bars + B_WPHI);
        tma_2d(sbase + OFF_WPHI + 4096, &prm.tmWphi, 0, 64 * g + 512, bars + B_WPHI);
        int stage = 0;
        uint32_t phase = 1;
        unsigned epoch = 0;
        for (int tile = 0; tile < 7; tile++) {
          const int nkb = (tile == 5) ? 32 : 16;
          if (tile == 5) {
            mbar_wait(bars + B_EPOCH, 0);
            asm volatile("ld.shared.u32 %0, [%1];" : "=r"(epoch) : "r"(bars + B_EPOCHV) : "memory");
            wait_ge(bars, &g_flags.hcnt[rb * 8], 16u * epoch);
          } else if (tile == 6) {
            wait_ge(bars, &g_flags.ocnt[2 * rb * 8], 8u * epoch);
          }
          for (int kb = 0; kb < nkb; kb++) {
            if (tile == 6 && kb == 8) wait_ge(bars, &g_flags.ocnt[(2 * rb + 1) * 8], 8u * epoch);
            mbar_wait(bars + B_EMPTY + 8 * stage, phase);
            const uint32_t full = bars + 8 * stage;
            const uint32_t sw = sbase + stage * STAGE_BYTES, sx = sw + 16384, swr = sw + rank * 8192;
            mbar_expect_tx(full, STAGE_BYTES);
            if (tile < 2) {
              tma_2d_mc(swr, rank ? &prm.tmBim : &prm.tmBre, kb * 64, 64 * (g + 8 * tile), full);
              tma_5d(sx, &prm.tmXB, kb * 64, 0, 0, 0, rb, full);
            } else if (tile < 4) {
              tma_2d_mc(swr, &prm.tmWqkv, 1024 + rank * 1024 + 64 * (g + 8 * (tile - 2)), kb * 64, full);
              tma_2d(sx, &prm.tmXA, kb * 64, rb * 128, full);
            } else if (tile == 4) {
              tma_2d_mc(swr, &prm.tmWqkv, 64 * (g + 8 * rank), kb * 64, full);
              tma_2d(sx, &prm.tmXA, kb * 64, rb * 128, full);
            } else if (tile == 5) {
              tma_2d_mc(swr, kb < 16 ? &prm.tmCre : &prm.tmCim, (kb & 15) * 64, 128 * g + 64 * rank, full);
              tma_3d(sx, &prm.tmHT, 0, kb * 64, 2 * rb, full);
            } else {
              tma_2d_mc(swr, &prm.tmWo, 128 * g + 64 * rank, kb * 64, full);
              tma_2d(sx, &prm.tmO, kb * 64, rb * 128, full);
            }
            if (++stage == STAGES) { stage = 0; phase ^= 1; }
          }
        }
        TSTAMP(1);
      }
    } else if (warp == 1) {
      unsigned epoch = 0;
      if (lane == 0) {
        epoch = (atomicAdd(&g_flags.ticket, 1u) >> 7) + 1u;
        asm volatile("st.shared.u32 [%0], %1;" ::"r"(bars + B_EPOCHV), "r"(epoch) : "memory");
        mbar_arrive(bars + B_EPOCH);
      }
      uint4* z = reinterpret_cast<uint4*>(g_kv) + blockIdx.x * 160;
#pragma unroll
      for (int i = 0; i < 5; i++) __stcg(z + i * 32 + lane, make_uint4(0, 0, 0, 0));
      __syncwarp();
      if (lane == 0) {
        red_release_add(&g_flags.zero_cnt, 1);
        store_agent(prm, sbase, g, rb, epoch);
      }
    } else {
#pragma unroll 1
      for (int c = 0; c < 2; c++) {
        const int ch = tid - 64, p = 64 * (g + 8 * c) + ch;
        const ChanParams cp = chan_params(__bfloat162float(prm.lam_re[p]), __bfloat162float(prm.lam_im[p]), __bfloat162float(prm.log_dt[p]));
        asm volatile("st.shared.v4.f32 [%0], {%1, %2, %3, %4};" ::"r"(sbase + OFF_V + (c * 64 + ch) * 16), "f"(cp.lam.r), "f"(cp.lam.i),
                     "f"(cp.c2.r), "f"(cp.c2.i) : "memory");
      }
      __syncwarp();
      if (lane == 0) mbar_arrive(bars + B_PARAM);
      unsigned epoch;
      mbar_wait(bars + B_EPOCH, 0);
      asm volatile("ld.shared.u32 %0, [%1];" : "=r"(epoch) : "r"(bars + B_EPOCHV) : "memory");
      helper_kv(sbase, g, epoch);
    }
    __syncwarp();
    asm volatile("barrier.cluster.arrive.relaxed.aligned;\nbarrier.cluster.wait.aligned;" ::: "memory");
  } else {
    reg_alloc<224>();
    const int cw = wg - 1;
    const int t = tid & 127, lane = t & 31, w = t >> 5, r8 = lane >> 2;
    float acc0[64], acc1[64];
    unsigned epoch;
    {
      const int G = g + 8 * cw;
      ChanParams cp[2];
      mbar_wait(bars + B_PARAM, 0);
#pragma unroll
      for (int c = 0; c < 2; c++) {
        const float4 v = lds128(sbase + OFF_V + (cw * 64 + 16 * w + r8 + 8 * c) * 16);
        cp[c].lam = {v.x, v.y};
        cp[c].c2 = {v.z, v.w};
      }
      TSTAMP(2 + 12 * cw);
      mainloop<0>(acc0, acc1, 16 * cw, 16, sbase, cw, cw ^ 1);
      TSTAMP(3 + 12 * cw);
      mbar_wait(bars + B_EPOCH, 0);
      asm volatile("ld.shared.u32 %0, [%1];" : "=r"(epoch) : "r"(bars + B_EPOCHV) : "memory");
      epi_bu(acc0, acc1, cp, sbase, G, rb, cw, epoch);
      TSTAMP(4 + 12 * cw);
    }
#pragma unroll 1
    for (int step = 0; step < 3; step++) {
      const int it0 = cw ? 48 : (step == 0 ? 32 : (step == 1 ? 64 : 112));
      mainloop<1>(acc0, acc1, it0, 16, sbase, cw, cw ? 1 : (step & 1));
      TSTAMP(step == 0 ? 5 + 12 * cw : (step == 1 ? 7 : 9));
      if (step == 2) {
        store_tile<false>(acc0, acc1, sbase + w * 16 * OST, prm, rb, g);
        TSTAMP(10);
        break;
      }
      mbar_wait(bars + B_WPHI, 0);
      mbar_wait(bars + B_EBF, cw ^ 1);
      epi_attn(acc0, acc1, sbase, cw, step == 1);
      TSTAMP(step == 0 ? 6 + 12 * cw : 8);
      if (cw == 1) break;
    }
    if (cw == 1) {
      mainloop<2>(acc0, acc1, 80, 32, sbase, 1, 0);
      TSTAMP(19);
      mbar_wait(bars + B_EBF, 0);
      store_tile<true>(acc0, acc1, sbase + OFF_EB + w * 16 * OST, prm, rb, g);
      TSTAMP(20);
    }
    asm volatile("barrier.cluster.arrive.relaxed.aligned;\nbarrier.cluster.wait.aligned;" ::: "memory");
  }
}

typedef CUresult (*PFN_encodeTiled)(CUtensorMap*, CUtensorMapDataType, cuuint32_t, void*, const cuuint64_t*, const cuuint64_t*,
                                    const cuuint32_t*, const cuuint32_t*, CUtensorMapInterleave, CUtensorMapSwizzle,
                                    CUtensorMapL2promotion, CUtensorMapFloatOOBfill);

bool make_tm(PFN_encodeTiled enc, CUtensorMap* tm, const void* base, int rank, const uint64_t* dims, const uint64_t* strides,
             const uint32_t* box, CUtensorMapSwizzle sw) {
  cuuint64_t gd[5], gs[5];
  cuuint32_t bx[5], es[5];
  for (int i = 0; i < rank; i++) { gd[i] = dims[i]; bx[i] = box[i]; es[i] = 1; }
  for (int i = 0; i + 1 < rank; i++) gs[i] = strides[i];
  return enc(tm, CU_TENSOR_MAP_DATA_TYPE_BFLOAT16, rank, const_cast<void*>(base), gd, gs, bx, es, CU_TENSOR_MAP_INTERLEAVE_NONE, sw,
             CU_TENSOR_MAP_L2_PROMOTION_L2_256B, CU_TENSOR_MAP_FLOAT_OOB_FILL_NONE) == CUDA_SUCCESS;
}
bool make_tm2(PFN_encodeTiled enc, CUtensorMap* tm, const void* base, uint64_t inner, uint64_t outer, uint32_t b0, uint32_t b1,
              CUtensorMapSwizzle sw = CU_TENSOR_MAP_SWIZZLE_128B) {
  const uint64_t dims[2] = {inner, outer}, str[1] = {inner * 2};
  const uint32_t box[2] = {b0, b1};
  return make_tm(enc, tm, base, 2, dims, str, box, sw);
}

}

extern "C" void kernel_launch(void* const* d_in, const int* in_sizes, int n_in, void* d_out, int out_size) {
  (void)in_sizes; (void)n_in; (void)out_size;
  static PFN_encodeTiled enc = nullptr;
  static void *pHT = nullptr, *pO = nullptr;
  if (!enc) {
    void* fn = nullptr;
    cudaDriverEntryPointQueryResult qr;
    if (cudaGetDriverEntryPoint("cuTensorMapEncodeTiled", &fn, cudaEnableDefault, &qr) != cudaSuccess || !fn) return;
    enc = (PFN_encodeTiled)fn;
    cudaFuncSetAttribute(fused_kernel, cudaFuncAttributeMaxDynamicSharedMemorySize, SMEM_BYTES);
    cudaGetSymbolAddress(&pHT, g_HT);
    cudaGetSymbolAddress(&pO, g_O);
  }
  Params prm;
  bool ok = true;
  {
    const uint64_t dims[5] = {1024, 2, 4, 16, 16}, str[4] = {2048, 65536, 4096, 262144};
    const uint32_t box[5] = {64, 2, 4, 16, 1};
    ok &= make_tm(enc, &prm.tmXB, d_in[4], 5, dims, str, box, CU_TENSOR_MAP_SWIZZLE_128B);
  }
  ok &= make_tm2(enc, &prm.tmBre, d_in[7], 1024, 1024, 64, 64);
  ok &= make_tm2(enc, &prm.tmBim, d_in[8], 1024, 1024, 64, 64);
  ok &= make_tm2(enc, &prm.tmXA, d_in[0], 1024, 2048, 64, 128);
  ok &= make_tm2(enc, &prm.tmWqkv, d_in[1], 3072, 1024, 64, 64);
  ok &= make_tm2(enc, &prm.tmWphi, d_in[2], 32, 1024, 32, 64, CU_TENSOR_MAP_SWIZZLE_64B);
  {
    const uint64_t dims[3] = {64, 2048, 32}, str[2] = {4096, 128};
    const uint32_t box[3] = {64, 64, 2};
    ok &= make_tm(enc, &prm.tmHT, pHT, 3, dims, str, box, CU_TENSOR_MAP_SWIZZLE_128B);
  }
  ok &= make_tm2(enc, &prm.tmCre, d_in[9], 1024, 1024, 64, 64);
  ok &= make_tm2(enc, &prm.tmCim, d_in[10], 1024, 1024, 64, 64);
  ok &= make_tm2(enc, &prm.tmO, pO, 1024, 2048, 64, 128);
  ok &= make_tm2(enc, &prm.tmWo, d_in[3], 1024, 1024, 64, 64);
  if (!ok) return;
  prm.xB = (const __nv_bfloat16*)d_in[4];
  prm.lam_re = (const __nv_bfloat16*)d_in[5];
  prm.lam_im = (const __nv_bfloat16*)d_in[6];
  prm.log_dt = (const __nv_bfloat16*)d_in[11];
  prm.dskip = (const __nv_bfloat16*)d_in[12];
  prm.out = (float*)d_out;

  cudaLaunchConfig_t cfg = {};
  cfg.gridDim = dim3(128);
  cfg.blockDim = dim3(384);
  cfg.dynamicSmemBytes = SMEM_BYTES;
  cfg.stream = cudaStreamPerThread;
  cudaLaunchAttribute attr[1];
  attr[0].id = cudaLaunchAttributeClusterDimension;
  attr[0].val.clusterDim.x = 2; attr[0].val.clusterDim.y = 1; attr[0].val.clusterDim.z = 1;
  cfg.attrs = attr;
  cfg.numAttrs = 1;
  cudaLaunchKernelEx(&cfg, fused_kernel, prm);
}
```

```cpp
#include <cuda_runtime.h>
#include <cuda_bf16.h>
#include <cuda.h>
#include <stdint.h>
#include <type_traits>

namespace {

constexpr int SEQ = 2048;
constexpr int DM = 1024;
#define NSTAGES 5
constexpr int STAGES = NSTAGES;
constexpr int STAGE_BYTES = 32768;
constexpr int OFF_EB = 5 * STAGE_BYTES;
constexpr int OFF_PHI = OFF_EB;
constexpr int OFF_V = OFF_EB + 32768;
constexpr int OFF_WPHI = OFF_EB + 53248;
constexpr int OFF_ONES = OFF_EB + 61440;
constexpr int OFF_BAR = OFF_EB + 62464;
constexpr int SMEM_BYTES = OFF_BAR + 256 + 1024;
constexpr int B_EMPTY = 64, B_ORD = 128, B_EBF = 144, B_WPHI = 152, B_EPOCH = 160, B_KVX = 168  , B_E3 = 184, B_EPOCHV = 192, B_DEAD = 196, B_JOB = 200  , B_PARAM = 248;

constexpr int KVW = 40;

struct Params {
  CUtensorMap tmXB;
  CUtensorMap tmBre, tmBim;
  CUtensorMap tmXA;
  CUtensorMap tmWqkv;
  CUtensorMap tmWphi;
  CUtensorMap tmHT;
  CUtensorMap tmCre, tmCim;
  CUtensorMap tmO;
  CUtensorMap tmWo;
  const __nv_bfloat16* xB;
  const __nv_bfloat16* lam_re;
  const __nv_bfloat16* lam_im;
  const __nv_bfloat16* log_dt;
  const __nv_bfloat16* dskip;
  float* out;
};

__device__ __nv_bfloat16 g_HT[2048 * 2048];
__device__ __nv_bfloat16 g_O[SEQ * DM];
__device__ float g_kv[32 * 64 * KVW];
__device__ uint4 g_E[16 * 16 * 64];
struct Flags {
  unsigned ticket;   unsigned pad0[31];
  unsigned zero_cnt; unsigned pad1[31];
  unsigned hcnt[16 * 8];
  unsigned kvcnt[16 * 8];
  unsigned ocnt[2 * 16 * 8];
};
__device__ Flags g_flags;
#define TSTAMP(i)
#define QT(i)

__device__ __forceinline__ uint32_t smem_u32(const void* p) { return (uint32_t)__cvta_generic_to_shared(p); }
__device__ __forceinline__ void mbar_init(uint32_t bar, uint32_t count) {
  asm volatile("mbarrier.init.shared::cta.b64 [%0], %1;" ::"r"(bar), "r"(count));
}
__device__ __forceinline__ void mbar_expect_tx(uint32_t bar, uint32_t bytes) {
  asm volatile("mbarrier.arrive.expect_tx.shared::cta.b64 _, [%0], %1;" ::"r"(bar), "r"(bytes) : "memory");
}
__device__ __forceinline__ void mbar_arrive(uint32_t bar) {
  asm volatile("mbarrier.arrive.shared::cta.b64 _, [%0];" ::"r"(bar) : "memory");
}
__device__ __forceinline__ void mbar_arrive_cluster(uint32_t bar, uint32_t cta) {
  asm volatile("{\n.reg .b32 ra;\nmapa.shared::cluster.u32 ra, %0, %1;\nmbarrier.arrive.shared::cluster.b64 _, [ra];\n}" ::"r"(bar), "r"(cta) : "memory");
}
__device__ __forceinline__ uint32_t dead_addr(uint32_t bar) { return (bar & ~0xFFu) + B_DEAD; }
__device__ __forceinline__ void mbar_wait(uint32_t bar, uint32_t parity) {
  asm volatile(
      "{\n.reg .pred p;\n.reg .u32 c, d;\n"
      "mov.u32 c, 0;\n"
      "WAIT_LOOP:\n"
      "mbarrier.try_wait.parity.shared::cta.b64 p, [%0], %1;\n"
      "@p bra WAIT_DONE;\n"
      "add.u32 c, c, 1;\n"
      "setp.gt.u32 p, c, 0x200000;\n"
      "@p st.volatile.shared.u32 [%2], c;\n"
      "ld.volatile.shared.u32 d, [%2];\n"
      "setp.eq.u32 p, d, 0;\n"
      "@p bra WAIT_LOOP;\n"
      "WAIT_DONE:\n}\n" ::"r"(bar), "r"(parity), "r"(dead_addr(bar)) : "memory");
}
__device__ __forceinline__ bool give_up(uint32_t bars, unsigned spins) {
  unsigned d;
  if (spins > (1u << 20)) asm volatile("st.volatile.shared.u32 [%0], %1;" ::"r"(bars + B_DEAD), "r"(spins) : "memory");
  asm volatile("ld.volatile.shared.u32 %0, [%1];" : "=r"(d) : "r"(bars + B_DEAD) : "memory");
  return d != 0;
}
__device__ __forceinline__ unsigned ld_relaxed(const unsigned* p) {
  unsigned v;
  asm volatile("ld.relaxed.gpu.global.u32 %0, [%1];" : "=r"(v) : "l"(p) : "memory");
  return v;
}
__device__ __forceinline__ void wait_ge(uint32_t bars, const unsigned* p, unsigned target) {
  unsigned spins = 0;
  while ((int)(ld_relaxed(p) - target) < 0) {
    __nanosleep(128);
    if (give_up(bars, ++spins)) break;
  }
}
__device__ __forceinline__ void red_release_add(unsigned* p, unsigned v) {
  asm volatile("red.release.gpu.global.add.u32 [%0], %1;" ::"l"(p), "r"(v) : "memory");
}
__device__ __forceinline__ void red_relaxed_add(unsigned* p, unsigned v) {
  asm volatile("red.relaxed.gpu.global.add.u32 [%0], %1;" ::"l"(p), "r"(v) : "memory");
}
__device__ __forceinline__ void st_tagged(uint4* p, float a, float b, unsigned tag) {
  const unsigned long long w0 = ((unsigned long long)tag << 32) | __float_as_uint(a);
  const unsigned long long w1 = ((unsigned long long)tag << 32) | __float_as_uint(b);
  asm volatile("st.relaxed.gpu.global.v2.b64 [%0], {%1, %2};" ::"l"(p), "l"(w0), "l"(w1) : "memory");
}
__device__ __forceinline__ void bulk_commit() { asm volatile("cp.async.bulk.commit_group;" ::: "memory"); }
__device__ __forceinline__ void bulk_wait_read() { asm volatile("cp.async.bulk.wait_group.read 0;" ::: "memory"); }
__device__ __forceinline__ void bulk_wait_all() { asm volatile("cp.async.bulk.wait_group 0;" ::: "memory"); }
__device__ __forceinline__ void bulk_reduce_f32(float* dst, uint32_t src, uint32_t bytes) {
  asm volatile("cp.reduce.async.bulk.global.shared::cta.bulk_group.add.f32 [%0], [%1], %2;" ::"l"(dst), "r"(src), "r"(bytes) : "memory");
}
__device__ __forceinline__ void tma_store_3d(const CUtensorMap* tm, uint32_t src, int c0, int c1, int c2) {
  asm volatile("cp.async.bulk.tensor.3d.global.shared::cta.bulk_group [%0, {%2, %3, %4}], [%1];"
               ::"l"(tm), "r"(src), "r"(c0), "r"(c1), "r"(c2) : "memory");
}
__device__ __forceinline__ void fence_async_smem() { asm volatile("fence.proxy.async.shared::cta;" ::: "memory"); }
__device__ __forceinline__ void tma_2d(uint32_t dst, const CUtensorMap* tm, int c0, int c1, uint32_t bar) {
  asm volatile("cp.async.bulk.tensor.2d.shared::cluster.global.mbarrier::complete_tx::bytes [%0], [%1, {%3, %4}], [%2];"
               ::"r"(dst), "l"(tm), "r"(bar), "r"(c0), "r"(c1) : "memory");
}
__device__ __forceinline__ void tma_3d(uint32_t dst, const CUtensorMap* tm, int c0, int c1, int c2, uint32_t bar) {
  asm volatile("cp.async.bulk.tensor.3d.shared::cluster.global.mbarrier::complete_tx::bytes [%0], [%1, {%3, %4, %5}], [%2];"
               ::"r"(dst), "l"(tm), "r"(bar), "r"(c0), "r"(c1), "r"(c2) : "memory");
}
__device__ __forceinline__ void tma_5d(uint32_t dst, const CUtensorMap* tm, int c0, int c1, int c2, int c3, int c4, uint32_t bar) {
  asm volatile("cp.async.bulk.tensor.5d.shared::cluster.global.mbarrier::complete_tx::bytes [%0], [%1, {%3, %4, %5, %6, %7}], [%2];"
               ::"r"(dst), "l"(tm), "r"(bar), "r"(c0), "r"(c1), "r"(c2), "r"(c3), "r"(c4) : "memory");
}
__device__ __forceinline__ void tma_2d_mc(uint32_t dst, const CUtensorMap* tm, int c0, int c1, uint32_t bar) {
  asm volatile("cp.async.bulk.tensor.2d.shared::cluster.global.mbarrier::complete_tx::bytes.multicast::cluster [%0], [%1, {%3, %4}], [%2], %5;"
               ::"r"(dst), "l"(tm), "r"(bar), "r"(c0), "r"(c1), "h"((uint16_t)3) : "memory");
}
__device__ __forceinline__ void tma_store_2d(const CUtensorMap* tm, uint32_t src, int c0, int c1) {
  asm volatile("cp.async.bulk.tensor.2d.global.shared::cta.bulk_group [%0, {%2, %3}], [%1];"
               ::"l"(tm), "r"(src), "r"(c0), "r"(c1) : "memory");
}
__device__ __forceinline__ bool elect_one() {
  uint32_t p;
  asm volatile("{\n.reg .pred e;\nelect.sync _|e, 0xffffffff;\nselp.u32 %0, 1, 0, e;\n}" : "=r"(p));
  return p != 0;
}
__device__ __forceinline__ void prefetch_tm(const CUtensorMap* tm) {
  asm volatile("prefetch.tensormap [%0];" ::"l"(tm) : "memory");
}
__device__ __forceinline__ void wgmma_fence() { asm volatile("wgmma.fence.sync.aligned;" ::: "memory"); }
__device__ __forceinline__ void wgmma_commit() { asm volatile("wgmma.commit_group.sync.aligned;" ::: "memory"); }
template <int N> __device__ __forceinline__ void wgmma_wait() { asm volatile("wgmma.wait_group.sync.aligned %0;" ::"n"(N) : "memory"); }
__device__ __forceinline__ void wg_bar(int id) {
  if (id == 1) asm volatile("bar.sync 1, 128;" ::: "memory");
  else asm volatile("bar.sync 2, 128;" ::: "memory");
}
template <int R> __device__ __forceinline__ void reg_alloc() { asm volatile("setmaxnreg.inc.sync.aligned.u32 %0;" ::"n"(R)); }
template <int R> __device__ __forceinline__ void reg_dealloc() { asm volatile("setmaxnreg.dec.sync.aligned.u32 %0;" ::"n"(R)); }

__device__ __forceinline__ uint64_t make_desc(uint32_t saddr, uint32_t lbo_bytes, uint32_t sbo_bytes, uint32_t layout) {
  uint64_t d = (uint64_t)((saddr & 0x3FFFF) >> 4);
  d |= (uint64_t)((lbo_bytes & 0x3FFFF) >> 4) << 16;
  d |= (uint64_t)((sbo_bytes & 0x3FFFF) >> 4) << 32;
  d |= (uint64_t)layout << 62;
  return d;
}
__device__ __forceinline__ uint64_t desc128(uint32_t lo) { return ((uint64_t)0x40000040u << 32) | lo; }
__device__ __forceinline__ uint32_t pack_bf16(float lo, float hi) {
  uint32_t r;
  asm("cvt.rn.bf16x2.f32 %0, %1, %2;" : "=r"(r) : "f"(hi), "f"(lo));
  return r;
}
__device__ __forceinline__ float ex2(float x) { float y; asm("ex2.approx.ftz.f32 %0, %1;" : "=f"(y) : "f"(x)); return y; }
__device__ __forceinline__ float rcp(float x) { float y; asm("rcp.approx.ftz.f32 %0, %1;" : "=f"(y) : "f"(x)); return y; }
__device__ __forceinline__ void stmatrix_x4(uint32_t addr, uint32_t r0, uint32_t r1, uint32_t r2, uint32_t r3) {
  asm volatile("stmatrix.sync.aligned.m8n8.x4.shared.b16 [%0], {%1, %2, %3, %4};" ::"r"(addr), "r"(r0), "r"(r1), "r"(r2), "r"(r3) : "memory");
}
template <int N> __device__ __forceinline__ void fence_regs(float (&d)[N]) {
#pragma unroll
  for (int i = 0; i < N; i++) asm volatile("" : "+f"(d[i])::"memory");
}

template <int TA, int TB>
__device__ __forceinline__ void wgmma_m64n128k16_ss(float (&d)[64], uint64_t descA, uint64_t descB) {
  asm volatile("{\n.reg .pred p;\nsetp.ne.b32 p, 1, 0;\n"
    "wgmma.mma_async.sync.aligned.m64n128k16.f32.bf16.bf16 "
    "{%0, %1, %2, %3, %4, %5, %6, %7, %8, %9, %10, %11, %12, %13, %14, %15, %16, %17, %18, %19, %20, %21, %22, %23, %24, %25, %26, %27, %28, %29, %30, %31, %32, %33, %34, %35, %36, %37, %38, %39, %40, %41, %42, %43, %44, %45, %46, %47, %48, %49, %50, %51, %52, %53, %54, %55, %56, %57, %58, %59, %60, %61, %62, %63}, "
    "%64, %65, p, 1, 1, %66, %67;\n}\n"
    : "+f"(d[0]), "+f"(d[1]), "+f"(d[2]), "+f"(d[3]), "+f"(d[4]), "+f"(d[5]), "+f"(d[6]), "+f"(d[7]), "+f"(d[8]), "+f"(d[9]), "+f"(d[10]), "+f"(d[11]), "+f"(d[12]), "+f"(d[13]), "+f"(d[14]), "+f"(d[15]), "+f"(d[16]), "+f"(d[17]), "+f"(d[18]), "+f"(d[19]), "+f"(d[20]), "+f"(d[21]), "+f"(d[22]), "+f"(d[23]), "+f"(d[24]), "+f"(d[25]), "+f"(d[26]), "+f"(d[27]), "+f"(d[28]), "+f"(d[29]), "+f"(d[30]), "+f"(d[31]), "+f"(d[32]), "+f"(d[33]), "+f"(d[34]), "+f"(d[35]), "+f"(d[36]), "+f"(d[37]), "+f"(d[38]), "+f"(d[39]), "+f"(d[40]), "+f"(d[41]), "+f"(d[42]), "+f"(d[43]), "+f"(d[44]), "+f"(d[45]), "+f"(d[46]), "+f"(d[47]), "+f"(d[48]), "+f"(d[49]), "+f"(d[50]), "+f"(d[51]), "+f"(d[52]), "+f"(d[53]), "+f"(d[54]), "+f"(d[55]), "+f"(d[56]), "+f"(d[57]), "+f"(d[58]), "+f"(d[59]), "+f"(d[60]), "+f"(d[61]), "+f"(d[62]), "+f"(d[63])
    : "l"(descA), "l"(descB), "n"(TA), "n"(TB));
}

template <int TA, int TB>
__device__ __forceinline__ void wgmma_m64n32k16_ss(float (&d)[16], uint64_t descA, uint64_t descB) {
  asm volatile("{\n.reg .pred p;\nsetp.ne.b32 p, 1, 0;\n"
    "wgmma.mma_async.sync.aligned.m64n32k16.f32.bf16.bf16 "
    "{%0, %1, %2, %3, %4, %5, %6, %7, %8, %9, %10, %11, %12, %13, %14, %15}, "
    "%16, %17, p, 1, 1, %18, %19;\n}\n"
    : "+f"(d[0]), "+f"(d[1]), "+f"(d[2]), "+f"(d[3]), "+f"(d[4]), "+f"(d[5]), "+f"(d[6]), "+f"(d[7]), "+f"(d[8]), "+f"(d[9]), "+f"(d[10]), "+f"(d[11]), "+f"(d[12]), "+f"(d[13]), "+f"(d[14]), "+f"(d[15])
    : "l"(descA), "l"(descB), "n"(TA), "n"(TB));
}

template <int TA, int TB>
__device__ __forceinline__ void wgmma_m64n32k16_ss_init(float (&d)[16], uint64_t descA, uint64_t descB) {
  asm volatile("{\n.reg .pred p;\nsetp.ne.b32 p, 0, 0;\n"
    "wgmma.mma_async.sync.aligned.m64n32k16.f32.bf16.bf16 "
    "{%0, %1, %2, %3, %4, %5, %6, %7, %8, %9, %10, %11, %12, %13, %14, %15}, "
    "%16, %17, p, 1, 1, %18, %19;\n}\n"
    : "=f"(d[0]), "=f"(d[1]), "=f"(d[2]), "=f"(d[3]), "=f"(d[4]), "=f"(d[5]), "=f"(d[6]), "=f"(d[7]), "=f"(d[8]), "=f"(d[9]), "=f"(d[10]), "=f"(d[11]), "=f"(d[12]), "=f"(d[13]), "=f"(d[14]), "=f"(d[15])
    : "l"(descA), "l"(descB), "n"(TA), "n"(TB));
}

template <int TA, int TB>
__device__ __forceinline__ void wgmma_m64n40k16_ss(float (&d)[20], uint64_t descA, uint64_t descB) {
  asm volatile("{\n.reg .pred p;\nsetp.ne.b32 p, 1, 0;\n"
    "wgmma.mma_async.sync.aligned.m64n40k16.f32.bf16.bf16 "
    "{%0, %1, %2, %3, %4, %5, %6, %7, %8, %9, %10, %11, %12, %13, %14, %15, %16, %17, %18, %19}, "
    "%20, %21, p, 1, 1, %22, %23;\n}\n"
    : "+f"(d[0]), "+f"(d[1]), "+f"(d[2]), "+f"(d[3]), "+f"(d[4]), "+f"(d[5]), "+f"(d[6]), "+f"(d[7]), "+f"(d[8]), "+f"(d[9]), "+f"(d[10]), "+f"(d[11]), "+f"(d[12]), "+f"(d[13]), "+f"(d[14]), "+f"(d[15]), "+f"(d[16]), "+f"(d[17]), "+f"(d[18]), "+f"(d[19])
    : "l"(descA), "l"(descB), "n"(TA), "n"(TB));
}

template <int TA, int TB>
__device__ __forceinline__ void wgmma_m64n40k16_ss_init(float (&d)[20], uint64_t descA, uint64_t descB) {
  asm volatile("{\n.reg .pred p;\nsetp.ne.b32 p, 0, 0;\n"
    "wgmma.mma_async.sync.aligned.m64n40k16.f32.bf16.bf16 "
    "{%0, %1, %2, %3, %4, %5, %6, %7, %8, %9, %10, %11, %12, %13, %14, %15, %16, %17, %18, %19}, "
    "%20, %21, p, 1, 1, %22, %23;\n}\n"
    : "=f"(d[0]), "=f"(d[1]), "=f"(d[2]), "=f"(d[3]), "=f"(d[4]), "=f"(d[5]), "=f"(d[6]), "=f"(d[7]), "=f"(d[8]), "=f"(d[9]), "=f"(d[10]), "=f"(d[11]), "=f"(d[12]), "=f"(d[13]), "=f"(d[14]), "=f"(d[15]), "=f"(d[16]), "=f"(d[17]), "=f"(d[18]), "=f"(d[19])
    : "l"(descA), "l"(descB), "n"(TA), "n"(TB));
}

template <int TB>
__device__ __forceinline__ void wgmma_m64n40k16_rs(float (&d)[20], uint32_t a0, uint32_t a1, uint32_t a2, uint32_t a3, uint64_t descB) {
  asm volatile("{\n.reg .pred p;\nsetp.ne.b32 p, 1, 0;\n"
    "wgmma.mma_async.sync.aligned.m64n40k16.f32.bf16.bf16 "
    "{%0, %1, %2, %3, %4, %5, %6, %7, %8, %9, %10, %11, %12, %13, %14, %15, %16, %17, %18, %19}, "
    "{%20, %21, %22, %23}, %24, p, 1, 1, %25;\n}\n"
    : "+f"(d[0]), "+f"(d[1]), "+f"(d[2]), "+f"(d[3]), "+f"(d[4]), "+f"(d[5]), "+f"(d[6]), "+f"(d[7]), "+f"(d[8]), "+f"(d[9]), "+f"(d[10]), "+f"(d[11]), "+f"(d[12]), "+f"(d[13]), "+f"(d[14]), "+f"(d[15]), "+f"(d[16]), "+f"(d[17]), "+f"(d[18]), "+f"(d[19])
    : "r"(a0), "r"(a1), "r"(a2), "r"(a3), "l"(descB), "n"(TB));
}

template <int TB>
__device__ __forceinline__ void wgmma_m64n40k16_rs_init(float (&d)[20], uint32_t a0, uint32_t a1, uint32_t a2, uint32_t a3, uint64_t descB) {
  asm volatile("{\n.reg .pred p;\nsetp.ne.b32 p, 0, 0;\n"
    "wgmma.mma_async.sync.aligned.m64n40k16.f32.bf16.bf16 "
    "{%0, %1, %2, %3, %4, %5, %6, %7, %8, %9, %10, %11, %12, %13, %14, %15, %16, %17, %18, %19}, "
    "{%20, %21, %22, %23}, %24, p, 1, 1, %25;\n}\n"
    : "=f"(d[0]), "=f"(d[1]), "=f"(d[2]), "=f"(d[3]), "=f"(d[4]), "=f"(d[5]), "=f"(d[6]), "=f"(d[7]), "=f"(d[8]), "=f"(d[9]), "=f"(d[10]), "=f"(d[11]), "=f"(d[12]), "=f"(d[13]), "=f"(d[14]), "=f"(d[15]), "=f"(d[16]), "=f"(d[17]), "=f"(d[18]), "=f"(d[19])
    : "r"(a0), "r"(a1), "r"(a2), "r"(a3), "l"(descB), "n"(TB));
}

template <int MODE>
__device__ __forceinline__ void mainloop(float (&acc0)[64], float (&acc1)[64], int it0, int nkb, uint32_t sbase, int cw,
                                         uint32_t ord_parity) {
  const uint32_t bars = sbase + OFF_BAR;
  const int lane = threadIdx.x & 31;
  int stage = it0 % STAGES;
  uint32_t phase = (it0 / STAGES) & 1;
#pragma unroll
  for (int i = 0; i < 64; i++) { acc0[i] = 0.f; acc1[i] = 0.f; }
  mbar_wait(bars + B_ORD + 8 * cw, ord_parity);
  int prev = 0;
  for (int kb = 0; kb < nkb; kb++) {
    mbar_wait(bars + 8 * stage, phase);
    if (kb == nkb - 1 && (threadIdx.x & 127) == 0) mbar_arrive(bars + B_ORD + 8 * (cw ^ 1));
    const uint32_t lo = ((sbase & 0x3FFFFu) + stage * STAGE_BYTES) >> 4;
    const uint32_t loK = lo | (1u << 16), loM = lo | (512u << 16);
    wgmma_fence();
#pragma unroll
    for (int k = 0; k < 4; k++) {
      if (MODE == 0) {
        const uint64_t dx = desc128(loK + 1024 + 2 * k);
        wgmma_m64n128k16_ss<0, 0>(acc0, desc128(loK + 2 * k), dx);
        wgmma_m64n128k16_ss<0, 0>(acc1, desc128(loK + 512 + 2 * k), dx);
      } else if (MODE == 1) {
        const uint64_t dw = desc128(loM + 128 * k);
        wgmma_m64n128k16_ss<0, 1>(acc0, desc128(loK + 1024 + 2 * k), dw);
        wgmma_m64n128k16_ss<0, 1>(acc1, desc128(loK + 1536 + 2 * k), dw);
      } else {
        const uint64_t dw = desc128(loK + 2 * k);
        wgmma_m64n128k16_ss<1, 0>(acc0, desc128(loM + 1024 + 128 * k), dw);
        wgmma_m64n128k16_ss<1, 0>(acc1, desc128(loM + 1536 + 128 * k), dw);
      }
    }
    wgmma_commit();
    wgmma_wait<1>();
    if (kb > 0 && lane < 2) mbar_arrive_cluster(bars + B_EMPTY + 8 * prev, lane);
    prev = stage;
    if (++stage == STAGES) { stage = 0; phase ^= 1; }
  }
  wgmma_wait<0>();
  if (lane < 2) mbar_arrive_cluster(bars + B_EMPTY + 8 * prev, lane);
  fence_regs(acc0);
  fence_regs(acc1);
}

template <int N>
__device__ __forceinline__ void dual_softmax_n(const float (&p)[N][16], uint32_t (&pos)[N][8], uint32_t (&neg)[N][8]) {
  constexpr float L2E = 1.4426950408889634f;
  float ca[N][2], cb[N][2];
  {
    float mx[N][2], mn[N][2];
#pragma unroll
    for (int i = 0; i < N; i++)
#pragma unroll
      for (int r = 0; r < 2; r++) {
        const int o = 2 * r;
        mx[i][r] = fmaxf(fmaxf(fmaxf(p[i][o], p[i][o + 1]), fmaxf(p[i][4 + o], p[i][5 + o])),
                         fmaxf(fmaxf(p[i][8 + o], p[i][9 + o]), fmaxf(p[i][12 + o], p[i][13 + o])));
        mn[i][r] = fminf(fminf(fminf(p[i][o], p[i][o + 1]), fminf(p[i][4 + o], p[i][5 + o])),
                         fminf(fminf(p[i][8 + o], p[i][9 + o]), fminf(p[i][12 + o], p[i][13 + o])));
      }
#pragma unroll
    for (int o = 1; o <= 2; o <<= 1) {
      float tx[N][2], tn[N][2];
#pragma unroll
      for (int i = 0; i < N; i++)
#pragma unroll
        for (int r = 0; r < 2; r++) { tx[i][r] = __shfl_xor_sync(0xffffffffu, mx[i][r], o); tn[i][r] = __shfl_xor_sync(0xffffffffu, mn[i][r], o); }
#pragma unroll
      for (int i = 0; i < N; i++)
#pragma unroll
        for (int r = 0; r < 2; r++) { mx[i][r] = fmaxf(mx[i][r], tx[i][r]); mn[i][r] = fminf(mn[i][r], tn[i][r]); }
    }
#pragma unroll
    for (int i = 0; i < N; i++)
#pragma unroll
      for (int r = 0; r < 2; r++) { ca[i][r] = -mx[i][r] * L2E; cb[i][r] = mn[i][r] * L2E; }
  }
  float ep[2][16], en[2][16];
  float rp[2], rn[2];
#pragma unroll
  for (int i = 0; i <= N; i++) {
    const int cur = i & 1, prv = cur ^ 1;
    if (i > 0) {
      float sp[2], sn[2];
#pragma unroll
      for (int r = 0; r < 2; r++) {
        const int o = 2 * r;
        sp[r] = ((ep[prv][o] + ep[prv][o + 1]) + (ep[prv][4 + o] + ep[prv][5 + o])) + ((ep[prv][8 + o] + ep[prv][9 + o]) + (ep[prv][12 + o] + ep[prv][13 + o]));
        sn[r] = ((en[prv][o] + en[prv][o + 1]) + (en[prv][4 + o] + en[prv][5 + o])) + ((en[prv][8 + o] + en[prv][9 + o]) + (en[prv][12 + o] + en[prv][13 + o]));
      }
      float t0[2], t1[2];
#pragma unroll
      for (int r = 0; r < 2; r++) { t0[r] = __shfl_xor_sync(0xffffffffu, sp[r], 1); t1[r] = __shfl_xor_sync(0xffffffffu, sn[r], 1); }
      if (i < N) {
#pragma unroll
        for (int e = 0; e < 4; e++) {
          ep[cur][e] = ex2(fmaf(p[i][e], L2E, ca[i][e >> 1])); en[cur][e] = ex2(fmaf(p[i][e], -L2E, cb[i][e >> 1]));
        }
      }
#pragma unroll
      for (int r = 0; r < 2; r++) { sp[r] += t0[r]; sn[r] += t1[r]; }
#pragma unroll
      for (int r = 0; r < 2; r++) { t0[r] = __shfl_xor_sync(0xffffffffu, sp[r], 2); t1[r] = __shfl_xor_sync(0xffffffffu, sn[r], 2); }
      if (i < N) {
#pragma unroll
        for (int e = 4; e < 8; e++) {
          ep[cur][e] = ex2(fmaf(p[i][e], L2E, ca[i][(e >> 1) & 1])); en[cur][e] = ex2(fmaf(p[i][e], -L2E, cb[i][(e >> 1) & 1]));
        }
      }
#pragma unroll
      for (int r = 0; r < 2; r++) { rp[r] = rcp(sp[r] + t0[r]); rn[r] = rcp(sn[r] + t1[r]); }
    } else {
#pragma unroll
      for (int e = 0; e < 8; e++) {
        ep[cur][e] = ex2(fmaf(p[i][e], L2E, ca[i][(e >> 1) & 1])); en[cur][e] = ex2(fmaf(p[i][e], -L2E, cb[i][(e >> 1) & 1]));
      }
    }
#pragma unroll
    for (int j = 0; j < 4; j++) {
      if (i < N && j >= 2) {
#pragma unroll
        for (int e = 4 * j; e < 4 * j + 4; e++) {
          ep[cur][e] = ex2(fmaf(p[i][e], L2E, ca[i][(e >> 1) & 1])); en[cur][e] = ex2(fmaf(p[i][e], -L2E, cb[i][(e >> 1) & 1]));
        }
      }
      if (i > 0) {
#pragma unroll
        for (int r = 0; r < 2; r++) {
          pos[i - 1][2 * j + r] = pack_bf16(ep[prv][4 * j + 2 * r] * rp[r], ep[prv][4 * j + 2 * r + 1] * rp[r]);
          neg[i - 1][2 * j + r] = pack_bf16(en[prv][4 * j + 2 * r] * rn[r], en[prv][4 * j + 2 * r + 1] * rn[r]);
        }
      }
    }
  }
}

struct cplx { float r, i; };
__device__ __forceinline__ cplx cmul(cplx a, cplx b) { return {a.r * b.r - a.i * b.i, a.r * b.i + a.i * b.r}; }
__device__ __forceinline__ cplx cfma(cplx a, cplx b, cplx c) {
  return {fmaf(a.r, b.r, fmaf(-a.i, b.i, c.r)), fmaf(a.r, b.i, fmaf(a.i, b.r, c.i))};
}
__device__ __forceinline__ cplx shfl_up_c(cplx v, int d) {
  return {__shfl_up_sync(0xffffffffu, v.r, d, 4), __shfl_up_sync(0xffffffffu, v.i, d, 4)};
}

struct ChanParams { cplx lam, c2; };

__device__ __forceinline__ ChanParams chan_params(float lr, float li, float log_dt) {
  const float dt = __bfloat162float(__float2bfloat16(expf(log_dt)));
  const float mag = expf(dt * lr);
  float sn, cs;
  sincosf(dt * li, &sn, &cs);
  ChanParams c;
  c.lam = {mag * cs, mag * sn};
  const float nr = c.lam.r - 1.0f, ni = c.lam.i;
  const float den = lr * lr + li * li;
  c.c2 = {2.0f * (nr * lr + ni * li) / den, 2.0f * (ni * lr - nr * li) / den};
  return c;
}

__device__ __forceinline__ void epi_bu(float (&are)[64], float (&aim)[64], const ChanParams (&cp)[2],
                                       uint32_t sbase, int G, int chunk, int cw, unsigned epoch) {
  const int lane = threadIdx.x & 31, w = (threadIdx.x & 127) >> 5, q = lane & 3, r8 = lane >> 2;
  cplx E[2] = {{0.f, 0.f}, {0.f, 0.f}};
#pragma unroll
  for (int k8 = 0; k8 < 16; k8++)
#pragma unroll
    for (int e = 0; e < 2; e++)
#pragma unroll
      for (int c = 0; c < 2; c++) E[c] = cfma(cp[c].lam, E[c], cplx{are[4 * k8 + 2 * c + e], aim[4 * k8 + 2 * c + e]});
  TSTAMP(32 + 4 * (threadIdx.x >> 8));
  cplx L32[2], L128[2], prev[2];
#pragma unroll
  for (int c = 0; c < 2; c++) {
    cplx l = cp[c].lam;
#pragma unroll
    for (int s = 0; s < 5; s++) l = cmul(l, l);
    L32[c] = l;
    const cplx l64 = cmul(l, l);
    L128[c] = cmul(l64, l64);
    cplx t = shfl_up_c(E[c], 1);
    if (q >= 1) E[c] = cfma(L32[c], t, E[c]);
    t = shfl_up_c(E[c], 2);
    if (q >= 2) E[c] = cfma(l64, t, E[c]);
    prev[c] = shfl_up_c(E[c], 1);
    if (q == 0) prev[c] = {0.f, 0.f};
  }
  uint4* gE = g_E + (size_t)G * 16 * 64 + 16 * w + r8;
  if (q == 3) {
    st_tagged(gE + chunk * 64, E[0].r, E[0].i, epoch);
    st_tagged(gE + chunk * 64 + 8, E[1].r, E[1].i, epoch);
  }
  cplx V[2][4];
  {
    unsigned long long w0[8], w1[8];
    unsigned pending = 0;
#pragma unroll
    for (int i = 0; i < 8; i++) {
      w0[i] = 0ull; w1[i] = 0ull;
      if (chunk - 1 - 4 * q - (i & 3) >= 0) pending |= 1u << i;
    }
    unsigned spins = 0;
    if (chunk > 0) __nanosleep(300);
    while (true) {
#pragma unroll
      for (int i = 0; i < 8; i++)
        asm volatile("{\n.reg .pred p;\nsetp.ne.u32 p, %3, 0;\n@p ld.relaxed.gpu.global.v2.b64 {%0, %1}, [%2];\n}"
                     : "+l"(w0[i]), "+l"(w1[i]) : "l"(gE + (chunk - 1 - 4 * q - (i & 3)) * 64 + 8 * (i >> 2)), "r"(pending & (1u << i)) : "memory");
#pragma unroll
      for (int i = 0; i < 8; i++)
        if ((unsigned)(w0[i] >> 32) == epoch && (unsigned)(w1[i] >> 32) == epoch) pending &= ~(1u << i);
      if (__all_sync(0xffffffffu, pending == 0)) break;
      __nanosleep(150);
      if (give_up(sbase + OFF_BAR, ++spins)) break;
    }
#pragma unroll
    for (int i = 0; i < 8; i++) V[i >> 2][i & 3] = {__uint_as_float((unsigned)w0[i]), __uint_as_float((unsigned)w1[i])};
  }
  TSTAMP(33 + 4 * (threadIdx.x >> 8));
  cplx s[2];
#pragma unroll
  for (int c = 0; c < 2; c++) {
    cplx Pq = V[c][3];
#pragma unroll
    for (int jj = 2; jj >= 0; jj--) Pq = cfma(L128[c], Pq, V[c][jj]);
    const cplx l256 = cmul(L128[c], L128[c]);
    const cplx l512 = cmul(l256, l256);
    cplx F = {1.f, 0.f};
    cplx G32 = {1.f, 0.f};
    if (q >= 1) { F = l512; G32 = L32[c]; }
    if (q >= 2) { F = cmul(F, l512); G32 = cmul(G32, L32[c]); }
    if (q >= 3) { F = cmul(F, l512); G32 = cmul(G32, L32[c]); }
    Pq = cmul(Pq, F);
#pragma unroll
    for (int o = 1; o <= 2; o <<= 1) {
      Pq.r += __shfl_xor_sync(0xffffffffu, Pq.r, o);
      Pq.i += __shfl_xor_sync(0xffffffffu, Pq.i, o);
    }
    s[c] = cfma(G32, Pq, prev[c]);
  }
  TSTAMP(34 + 4 * (threadIdx.x >> 8));
  if (cw == 1) mbar_wait(sbase + OFF_BAR + B_EBF, 0);
#pragma unroll
  for (int qq = 0; qq < 4; qq++) {
    uint32_t ore[2][4], oim[2][4];
#pragma unroll
    for (int kk = 0; kk < 4; kk++) {
      const int k8 = 4 * qq + kk;
      float hr[2][2], hi[2][2];
#pragma unroll
      for (int e = 0; e < 2; e++)
#pragma unroll
        for (int c = 0; c < 2; c++) {
          s[c] = cfma(cp[c].lam, s[c], cplx{are[4 * k8 + 2 * c + e], aim[4 * k8 + 2 * c + e]});
          hr[c][e] = fmaf(cp[c].c2.r, s[c].r, -cp[c].c2.i * s[c].i);
          hi[c][e] = -fmaf(cp[c].c2.r, s[c].i, cp[c].c2.i * s[c].r);
        }
#pragma unroll
      for (int c = 0; c < 2; c++) {
        ore[c][kk] = pack_bf16(hr[c][0], hr[c][1]);
        oim[c][kk] = pack_bf16(hi[c][0], hi[c][1]);
      }
    }
#pragma unroll
    for (int c = 0; c < 2; c++) {
      const int row = 16 * w + r8 + 8 * c;
      const uint32_t addr = sbase + OFF_PHI + (qq >> 1) * 8192 + row * 128 + ((((qq & 1) * 4 + q) ^ (row & 7)) << 4);
      asm volatile("st.shared.v4.b32 [%0], {%1, %2, %3, %4};" ::"r"(addr), "r"(ore[c][0]), "r"(ore[c][1]), "r"(ore[c][2]), "r"(ore[c][3]) : "memory");
      asm volatile("st.shared.v4.b32 [%0], {%1, %2, %3, %4};" ::"r"(addr + 16384), "r"(oim[c][0]), "r"(oim[c][1]), "r"(oim[c][2]), "r"(oim[c][3]) : "memory");
    }
  }
  TSTAMP(35 + 4 * (threadIdx.x >> 8));
  fence_async_smem();
  wg_bar(1 + cw);
  if ((threadIdx.x & 127) == 0) mbar_arrive(sbase + OFF_BAR + B_JOB + 8 * cw);
}

__device__ __forceinline__ void q_issue_num(float (&num)[20], const uint32_t (&pos)[8], const uint32_t (&neg)[8], uint32_t b) {
  wgmma_fence();
  wgmma_m64n40k16_rs_init<1>(num, pos[0], pos[1], pos[2], pos[3], make_desc(b, 640, 128, 0));
  wgmma_m64n40k16_rs<1>(num, pos[4], pos[5], pos[6], pos[7], make_desc(b + 1280, 640, 128, 0));
  wgmma_m64n40k16_rs<1>(num, neg[0], neg[1], neg[2], neg[3], make_desc(b + 2560, 640, 128, 0));
  wgmma_m64n40k16_rs<1>(num, neg[4], neg[5], neg[6], neg[7], make_desc(b + 3840, 640, 128, 0));
  wgmma_commit();
}
__device__ __forceinline__ void q_store_o(const float (&num)[20], uint32_t rowaddr, int chunk0) {
  const int lane = threadIdx.x & 31, mi = lane >> 3, rin = lane & 7;
  const float d0 = __shfl_sync(0xffffffffu, num[16], lane & ~3), d1 = __shfl_sync(0xffffffffu, num[18], lane & ~3);
  const float i0 = __fdividef(1.0f, d0 + 1e-6f), i1 = __fdividef(1.0f, d1 + 1e-6f);
#pragma unroll
  for (int jp = 0; jp < 2; jp++) {
    const int c0 = chunk0 + jp * 2 + (mi >> 1);
    stmatrix_x4(rowaddr + ((c0 ^ rin) << 4), pack_bf16(num[8 * jp] * i0, num[8 * jp + 1] * i0),
                pack_bf16(num[8 * jp + 2] * i1, num[8 * jp + 3] * i1), pack_bf16(num[8 * jp + 4] * i0, num[8 * jp + 5] * i0),
                pack_bf16(num[8 * jp + 6] * i1, num[8 * jp + 7] * i1));
  }
}
__device__ __forceinline__ void epi_attn(float (&acc0)[64], float (&acc1)[64], uint32_t sbase, int cw, bool isq) {
  const int t = threadIdx.x & 127, lane = t & 31, w = t >> 5, q = lane & 3, r8 = lane >> 2;
  const int mi = lane >> 3, rin = lane & 7;
  const int row0 = w * 16 + (mi & 1) * 8 + rin;
  {
    const uint32_t tile = sbase + OFF_PHI + (isq ? 0 : 16384) + row0 * 128;
#pragma unroll
    for (int j = 0; j < 8; j += 2) {
      const uint32_t addr = tile + (((j + (mi >> 1)) ^ rin) << 4);
      stmatrix_x4(addr, pack_bf16(acc0[4 * j], acc0[4 * j + 1]), pack_bf16(acc0[4 * j + 2], acc0[4 * j + 3]),
                  pack_bf16(acc0[4 * j + 4], acc0[4 * j + 5]), pack_bf16(acc0[4 * j + 6], acc0[4 * j + 7]));
      stmatrix_x4(addr + 8192, pack_bf16(acc1[4 * j], acc1[4 * j + 1]), pack_bf16(acc1[4 * j + 2], acc1[4 * j + 3]),
                  pack_bf16(acc1[4 * j + 4], acc1[4 * j + 5]), pack_bf16(acc1[4 * j + 6], acc1[4 * j + 7]));
    }
  }
#pragma unroll
  for (int j = 8; j < 16; j += 2) {
    const uint32_t aq = sbase + OFF_PHI + 16384 + row0 * 128 + (((j - 8 + (mi >> 1)) ^ rin) << 4);
    const uint32_t av = sbase + OFF_V + ((j - 8) >> 2) * 8192 + row0 * 64 + ((((j & 3) + (mi >> 1)) ^ ((row0 >> 1) & 3)) << 4);
    const uint32_t addr = isq ? aq : av;
    stmatrix_x4(addr, pack_bf16(acc0[4 * j], acc0[4 * j + 1]), pack_bf16(acc0[4 * j + 2], acc0[4 * j + 3]),
                pack_bf16(acc0[4 * j + 4], acc0[4 * j + 5]), pack_bf16(acc0[4 * j + 6], acc0[4 * j + 7]));
    stmatrix_x4(addr + (isq ? 8192 : 4096), pack_bf16(acc1[4 * j], acc1[4 * j + 1]), pack_bf16(acc1[4 * j + 2], acc1[4 * j + 3]),
                pack_bf16(acc1[4 * j + 4], acc1[4 * j + 5]), pack_bf16(acc1[4 * j + 6], acc1[4 * j + 7]));
  }
  fence_async_smem();
  wg_bar(1 + cw);
  TSTAMP(isq ? 56 : 40 + 8 * cw);
  const int nsub = isq ? 2 : 1;
#pragma unroll 1
  for (int sub = 0; sub < nsub; sub++) {
    const int it = 4 * sub;
    (void)it;
    const uint32_t tile = sbase + OFF_PHI + (isq ? sub : 1) * 16384;
    const uint32_t wp = sbase + OFF_WPHI + (isq ? 2 * sub : 2 * cw) * 2048;
    float pq[4][16];
    uint32_t pos[4][8], neg[4][8];
    QT(0);
    wgmma_fence();
#pragma unroll
    for (int i = 0; i < 4; i++) {
      const uint32_t a = tile + (i & 1) * 8192 + (i >> 1) * 64, b = wp + (i >> 1) * 2048;
      wgmma_m64n32k16_ss_init<0, 1>(pq[i], make_desc(a, 16, 1024, 1), make_desc(b, 512, 512, 2));
      wgmma_m64n32k16_ss<0, 1>(pq[i], make_desc(a + 32, 16, 1024, 1), make_desc(b + 1024, 512, 512, 2));
    }
    wgmma_commit();
    wgmma_wait<0>();
#pragma unroll
    for (int i = 0; i < 4; i++) fence_regs(pq[i]);
    QT(1);
    dual_softmax_n<4>(pq, pos, neg);
    QT(2);
    if (!isq) {
      float kvacc[2][20];
#pragma unroll
      for (int hh = 0; hh < 2; hh++) {
#pragma unroll
        for (int half = 0; half < 2; half++) {
          const uint32_t rb = sbase + OFF_PHI + hh * 16384 + (half * 64 + row0) * 128;
#pragma unroll
          for (int jp = 0; jp < 2; jp++) {
            const int c0 = jp * 2 + (mi >> 1), i = 2 * hh + half;
            stmatrix_x4(rb + ((c0 ^ rin) << 4), pos[i][4 * jp], pos[i][4 * jp + 1], pos[i][4 * jp + 2], pos[i][4 * jp + 3]);
            stmatrix_x4(rb + (((c0 + 4) ^ rin) << 4), neg[i][4 * jp], neg[i][4 * jp + 1], neg[i][4 * jp + 2], neg[i][4 * jp + 3]);
          }
        }
      }
      fence_async_smem();
      wg_bar(1 + cw);
      wgmma_fence();
#pragma unroll
      for (int hh = 0; hh < 2; hh++)
#pragma unroll
        for (int ks = 0; ks < 8; ks++) {
          const uint32_t vb = sbase + OFF_V + hh * 8192 + ks * 1024;
          const uint64_t da = make_desc(sbase + OFF_PHI + hh * 16384 + ks * 2048, 1024, 1024, 1);
          const uint64_t db = make_desc(vb, sbase + OFF_ONES - vb, 512, 2);
          if (ks == 0) wgmma_m64n40k16_ss_init<1, 1>(kvacc[hh], da, db);
          else wgmma_m64n40k16_ss<1, 1>(kvacc[hh], da, db);
        }
      wgmma_commit();
      TSTAMP(42 + 8 * cw);
      wgmma_wait<0>();
      fence_regs(kvacc[0]);
      fence_regs(kvacc[1]);
      TSTAMP(43 + 8 * cw);
      wg_bar(1 + cw);
#pragma unroll
      for (int hh = 0; hh < 2; hh++) {
        const uint32_t dst = sbase + OFF_PHI + hh * 16384 + ((16 * w + r8) * KVW + 2 * q) * 4;
#pragma unroll
        for (int j = 0; j < 5; j++) {
          asm volatile("st.shared.v2.f32 [%0], {%1, %2};" ::"r"(dst + 32 * j), "f"(kvacc[hh][4 * j]), "f"(kvacc[hh][4 * j + 1]) : "memory");
          asm volatile("st.shared.v2.f32 [%0], {%1, %2};" ::"r"(dst + 8 * KVW * 4 + 32 * j), "f"(kvacc[hh][4 * j + 2]), "f"(kvacc[hh][4 * j + 3]) : "memory");
        }
      }
      fence_async_smem();
      wg_bar(1 + cw);
      if (t == 0) mbar_arrive(sbase + OFF_BAR + B_JOB + 16 + 8 * cw);
      TSTAMP(44 + 8 * cw);
    } else {
      float num[4][20];
      mbar_wait(sbase + OFF_BAR + B_KVX + 8 * sub, 0);
      TSTAMP(57 + sub);
      QT(3);
#pragma unroll
      for (int i = 0; i < 4; i++) q_issue_num(num[i], pos[i], neg[i], sbase + OFF_V + (2 * sub + (i >> 1)) * 5120);
      QT(4);
      wgmma_wait<2>();
      fence_regs(num[0]); fence_regs(num[1]);
      QT(5);
      q_store_o(num[0], tile + row0 * 128, 0);
      q_store_o(num[1], tile + 8192 + row0 * 128, 0);
      wgmma_wait<0>();
      fence_regs(num[2]); fence_regs(num[3]);
      QT(6);
      q_store_o(num[2], tile + row0 * 128, 4);
      q_store_o(num[3], tile + 8192 + row0 * 128, 4);
      QT(7);
      fence_async_smem();
      wg_bar(1);
      if (t == 0) mbar_arrive(sbase + OFF_BAR + B_JOB + 32 + 8 * sub);
    }
  }
}

__device__ __forceinline__ void helper_kv(uint32_t sbase, int g, unsigned epoch) {
  const int h = threadIdx.x - 64;
  mbar_wait(sbase + OFF_BAR + B_E3, 0);
#pragma unroll 1
  for (int pr = 0; pr < 2; pr++) {
    if ((h & 31) == 0) wait_ge(sbase + OFF_BAR, &g_flags.kvcnt[(g + 8 * pr) * 8], 16u * epoch);
    __syncwarp();
    const float4* src = reinterpret_cast<const float4*>(g_kv + (size_t)(2 * g + 16 * pr) * 64 * KVW);
#pragma unroll 1
    for (int ib = 0; ib < 3; ib++) {
      float4 u[7];
#pragma unroll
      for (int i = 0; i < 7; i++) u[i] = __ldcg(src + min((ib * 7 + i) * 64 + h, 1279));
#pragma unroll
      for (int i = 0; i < 7; i++) {
        const int idx = min((ib * 7 + i) * 64 + h, 1279);
        const int f2 = idx / 10, j = idx - f2 * 10;
        const uint32_t dst = sbase + OFF_V + pr * 10240 + (f2 >> 3) * 640 + (j >> 1) * 128 + (f2 & 7) * 16 + (j & 1) * 8;
        asm volatile("st.shared.v2.b32 [%0], {%1, %2};" ::"r"(dst), "r"(pack_bf16(u[i].x, u[i].y)), "r"(pack_bf16(u[i].z, u[i].w)) : "memory");
      }
    }
    fence_async_smem();
    __syncwarp();
    if ((h & 31) == 0) mbar_arrive(sbase + OFF_BAR + B_KVX + 8 * pr);
  }
}

__device__ __forceinline__ void store_agent(const Params& prm, uint32_t sbase, int g, int rb, unsigned epoch) {
  const uint32_t bars = sbase + OFF_BAR;
#pragma unroll 1
  for (int j = 0; j < 6; j++) {
    mbar_wait(bars + B_JOB + 8 * j, 0);
    unsigned* flag;
    if (j < 2) {
      const int G = g + 8 * j;
      tma_store_3d(&prm.tmHT, sbase + OFF_PHI, 0, 64 * G, 2 * rb);
      tma_store_3d(&prm.tmHT, sbase + OFF_PHI + 16384, 0, 1024 + 64 * G, 2 * rb);
      flag = &g_flags.hcnt[rb * 8];
    } else if (j < 4) {
      const int hp = g + 8 * (j - 2);
      wait_ge(bars, &g_flags.zero_cnt, 128u * epoch);
      bulk_reduce_f32(g_kv + (size_t)(2 * hp) * 64 * KVW, sbase + OFF_PHI, 64 * KVW * 4);
      bulk_reduce_f32(g_kv + (size_t)(2 * hp + 1) * 64 * KVW, sbase + OFF_PHI + 16384, 64 * KVW * 4);
      flag = &g_flags.kvcnt[hp * 8];
    } else {
      tma_store_2d(&prm.tmO, sbase + OFF_PHI + (j - 4) * 16384, 64 * (g + 8 * (j - 4)), 128 * rb);
      flag = &g_flags.ocnt[(2 * rb + (j - 4)) * 8];
    }
    bulk_commit();
    if (j != 4) {
      bulk_wait_read();
      mbar_arrive(bars + B_EBF);
      if (j == 3) mbar_arrive(bars + B_E3);
    }
    bulk_wait_all();
    red_relaxed_add(flag, 1);
  }
}

constexpr int OST = 544;
__device__ __forceinline__ float bf16_round(float x) { return __bfloat162float(__float2bfloat16(x)); }
__device__ __forceinline__ void stage_half(const float (&a)[64], uint32_t wbuf) {
  const int lane = threadIdx.x & 31, q = lane & 3, r8 = lane >> 2;
#pragma unroll
  for (int j = 0; j < 16; j++) {
    asm volatile("st.shared.v2.f32 [%0], {%1, %2};" ::"r"(wbuf + r8 * OST + j * 32 + q * 8), "f"(a[4 * j]), "f"(a[4 * j + 1]) : "memory");
    asm volatile("st.shared.v2.f32 [%0], {%1, %2};" ::"r"(wbuf + (r8 + 8) * OST + j * 32 + q * 8), "f"(a[4 * j + 2]), "f"(a[4 * j + 3]) : "memory");
  }
  __syncwarp();
}
__device__ __forceinline__ float4 lds128(uint32_t addr) {
  float4 v;
  asm volatile("ld.shared.v4.f32 {%0, %1, %2, %3}, [%4];" : "=f"(v.x), "=f"(v.y), "=f"(v.z), "=f"(v.w) : "r"(addr) : "memory");
  return v;
}
template <bool IS_Y>
__device__ __forceinline__ void store_tile(float (&acc0)[64], const float (&acc1)[64], uint32_t wbuf, const Params& prm, int rb, int g) {
  const int lane = threadIdx.x & 31, w = (threadIdx.x & 127) >> 5;
  uint2 dk = make_uint2(0, 0);
  if (IS_Y) dk = __ldg(reinterpret_cast<const uint2*>(prm.dskip + 128 * g) + lane);
#pragma unroll 1
  for (int half = 0; half < 2; half++) {
    const int m0 = 64 * half + 16 * w;
    const int t0 = rb * 128 + (IS_Y ? 32 * ((m0 >> 3) & 3) + 8 * (m0 >> 5) : m0);
    uint2 xs[16];
    if (IS_Y) {
#pragma unroll
      for (int r = 0; r < 16; r++)
        xs[r] = __ldg(reinterpret_cast<const uint2*>(prm.xB + (size_t)(t0 + (r & 7) + (r >> 3) * 32) * DM + 128 * g) + lane);
    }
    stage_half(acc0, wbuf);
    float* dst = prm.out + (size_t)t0 * 2048 + (IS_Y ? 1024 : 0) + 128 * g + 4 * lane;
#pragma unroll
    for (int r = 0; r < 16; r++) {
      float4 v = lds128(wbuf + r * OST + lane * 16);
      if (IS_Y) {
        const float2 s0 = __bfloat1622float2(__hmul2(*reinterpret_cast<const __nv_bfloat162*>(&xs[r].x), *reinterpret_cast<const __nv_bfloat162*>(&dk.x)));
        const float2 s1 = __bfloat1622float2(__hmul2(*reinterpret_cast<const __nv_bfloat162*>(&xs[r].y), *reinterpret_cast<const __nv_bfloat162*>(&dk.y)));
        v.x += s0.x; v.y += s0.y; v.z += s1.x; v.w += s1.y;
      } else {
        v.x = bf16_round(v.x); v.y = bf16_round(v.y); v.z = bf16_round(v.z); v.w = bf16_round(v.w);
      }
      __stcs(reinterpret_cast<float4*>(dst + (size_t)((r & 7) + (r >> 3) * (IS_Y ? 32 : 8)) * 2048), v);
    }
    __syncwarp();
#pragma unroll
    for (int i = 0; i < 64; i++) acc0[i] = acc1[i];
  }
}

__global__ void __launch_bounds__(384, 1) fused_kernel(const __grid_constant__ Params prm) {
  extern __shared__ uint8_t smem_raw[];
  const uint32_t sbase = (smem_u32(smem_raw) + 1023) & ~1023u;
  const uint32_t bars = sbase + OFF_BAR;
  const int tid = threadIdx.x, wg = __shfl_sync(0xffffffffu, tid >> 7, 0);
  const int cl = blockIdx.x >> 1, rank = blockIdx.x & 1;
  const int g = cl >> 3, rb = 2 * (cl & 7) + rank;

  if (tid == 0) {
    for (int s = 0; s < STAGES; s++) { mbar_init(bars + 8 * s, 1);
      mbar_init(bars + B_EMPTY + 8 * s, 8);
    }
    mbar_init(bars + B_ORD, 1); mbar_init(bars + B_ORD + 8, 1); mbar_init(bars + B_EBF, 1); mbar_init(bars + B_WPHI, 1); mbar_init(bars + B_EPOCH, 1); mbar_init(bars + B_KVX, 2); mbar_init(bars + B_KVX + 8, 2);
    for (int j = 0; j < 6; j++) mbar_init(bars + B_JOB + 8 * j, 1);
    mbar_init(bars + B_PARAM, 2); mbar_init(bars + B_E3, 1);
    asm volatile("st.shared.u32 [%0], %1;" ::"r"(bars + B_DEAD), "r"(0u) : "memory");
    asm volatile("fence.mbarrier_init.release.cluster;" ::: "memory");
  } else if (tid == 32) {
    prefetch_tm(&prm.tmXB); prefetch_tm(rank ? &prm.tmBim : &prm.tmBre); prefetch_tm(&prm.tmWphi);
    prefetch_tm(&prm.tmXA); prefetch_tm(&prm.tmWqkv); prefetch_tm(&prm.tmHT);
    prefetch_tm(&prm.tmCre); prefetch_tm(&prm.tmCim); prefetch_tm(&prm.tmO); prefetch_tm(&prm.tmWo);
  } else if (tid >= 64 && tid < 128) {
    asm volatile("st.shared.v4.b32 [%0], {%1, %2, %2, %2};" ::"r"(sbase + OFF_ONES + (tid - 64) * 16), "r"(0x00003F80u), "r"(0u) : "memory");
    fence_async_smem();
  }
  __syncthreads();
  asm volatile("barrier.cluster.arrive.relaxed.aligned;\nbarrier.cluster.wait.acquire.aligned;" ::: "memory");

  if (wg == 0) {
    reg_dealloc<56>();
    const int warp = __shfl_sync(0xffffffffu, tid >> 5, 0), lane = tid & 31;
    if (warp == 0) {
      const bool leader = elect_one();
      TSTAMP(0);
      if (leader) {
        mbar_expect_tx(bars + B_WPHI, 8192);
        tma_2d(sbase + OFF_WPHI, &prm.tmWphi, 0, 64 * g, bars + B_WPHI);
        tma_2d(sbase + OFF_WPHI + 4096, &prm.tmWphi, 0, 64 * g + 512, bars + B_WPHI);
      }
      int stage = 0;
      uint32_t phase = 1;
      unsigned epoch = 0;
      auto run = [&](auto kind, const CUtensorMap* tw, int w0, const CUtensorMap* tx, int kb0, int kb1) {
        constexpr int KIND = decltype(kind)::value;
#pragma unroll 1
        for (int kb = kb0; kb < kb1; kb++) {
          mbar_wait(bars + B_EMPTY + 8 * stage, phase);
          if (leader) {
            const uint32_t full = bars + 8 * stage;
            const uint32_t sw = sbase + stage * STAGE_BYTES;
            mbar_expect_tx(full, STAGE_BYTES);
            if (KIND == 0) {
              tma_2d_mc(sw + rank * 8192, tw, kb * 64, w0, full);
              tma_5d(sw + 16384, tx, kb * 64, 0, 0, 0, rb, full);
            } else if (KIND == 1) {
              tma_2d_mc(sw + rank * 8192, tw, w0, kb * 64, full);
              tma_2d(sw + 16384, tx, kb * 64, rb * 128, full);
            } else {
              tma_2d_mc(sw + rank * 8192, tw, (kb & 15) * 64, w0, full);
              tma_3d(sw + 16384, tx, 0, kb * 64, 2 * rb, full);
            }
          }
          if (++stage == STAGES) { stage = 0; phase ^= 1; }
        }
      };
      using K0 = std::integral_constant<int, 0>;
      using K1 = std::integral_constant<int, 1>;
      using K2 = std::integral_constant<int, 2>;
#pragma unroll 1
      for (int i = 0; i < 2; i++) run(K0{}, rank ? &prm.tmBim : &prm.tmBre, 64 * (g + 8 * i), &prm.tmXB, 0, 16);
#pragma unroll 1
      for (int i = 0; i < 3; i++)
        run(K1{}, &prm.tmWqkv, i < 2 ? 1024 + rank * 1024 + 64 * (g + 8 * i) : 64 * (g + 8 * rank), &prm.tmXA, 0, 16);
      mbar_wait(bars + B_EPOCH, 0);
      asm volatile("ld.shared.u32 %0, [%1];" : "=r"(epoch) : "r"(bars + B_EPOCHV) : "memory");
      wait_ge(bars, &g_flags.hcnt[rb * 8], 16u * epoch);
#pragma unroll 1
      for (int i = 0; i < 2; i++) run(K2{}, i ? &prm.tmCim : &prm.tmCre, 128 * g + 64 * rank, &prm.tmHT, 16 * i, 16 * i + 16);
#pragma unroll 1
      for (int i = 0; i < 2; i++) {
        wait_ge(bars, &g_flags.ocnt[(2 * rb + i) * 8], 8u * epoch);
        run(K1{}, &prm.tmWo, 128 * g + 64 * rank, &prm.tmO, 8 * i, 8 * i + 8);
      }
      TSTAMP(1);
    } else if (warp == 1) {
      unsigned epoch = 0;
      if (lane == 0) {
        epoch = (atomicAdd(&g_flags.ticket, 1u) >> 7) + 1u;
        asm volatile("st.shared.u32 [%0], %1;" ::"r"(bars + B_EPOCHV), "r"(epoch) : "memory");
        mbar_arrive(bars + B_EPOCH);
      }
      uint4* z = reinterpret_cast<uint4*>(g_kv) + blockIdx.x * 160;
#pragma unroll
      for (int i = 0; i < 5; i++) __stcg(z + i * 32 + lane, make_uint4(0, 0, 0, 0));
      __syncwarp();
      if (lane == 0) {
        red_release_add(&g_flags.zero_cnt, 1);
        store_agent(prm, sbase, g, rb, epoch);
      }
    } else {
#pragma unroll 1
      for (int c = 0; c < 2; c++) {
        const int ch = tid - 64, p = 64 * (g + 8 * c) + ch;
        const ChanParams cp = chan_params(__bfloat162float(prm.lam_re[p]), __bfloat162float(prm.lam_im[p]), __bfloat162float(prm.log_dt[p]));
        asm volatile("st.shared.v4.f32 [%0], {%1, %2, %3, %4};" ::"r"(sbase + OFF_V + (c * 64 + ch) * 16), "f"(cp.lam.r), "f"(cp.lam.i),
                     "f"(cp.c2.r), "f"(cp.c2.i) : "memory");
      }
      __syncwarp();
      if (lane == 0) mbar_arrive(bars + B_PARAM);
      unsigned epoch;
      mbar_wait(bars + B_EPOCH, 0);
      asm volatile("ld.shared.u32 %0, [%1];" : "=r"(epoch) : "r"(bars + B_EPOCHV) : "memory");
      helper_kv(sbase, g, epoch);
    }
    __syncwarp();
    asm volatile("barrier.cluster.arrive.relaxed.aligned;\nbarrier.cluster.wait.aligned;" ::: "memory");
  } else {
    reg_alloc<224>();
    const int cw = wg - 1;
    const int t = tid & 127, lane = t & 31, w = t >> 5, r8 = lane >> 2;
    float acc0[64], acc1[64];
    unsigned epoch;
    {
      const int G = g + 8 * cw;
      ChanParams cp[2];
      TSTAMP(2 + 12 * cw);
      mainloop<0>(acc0, acc1, 16 * cw, 16, sbase, cw, cw ^ 1);
      TSTAMP(3 + 12 * cw);
      mbar_wait(bars + B_PARAM, 0);
#pragma unroll
      for (int c = 0; c < 2; c++) {
        const float4 v = lds128(sbase + OFF_V + (cw * 64 + 16 * w + r8 + 8 * c) * 16);
        cp[c].lam = {v.x, v.y};
        cp[c].c2 = {v.z, v.w};
      }
      mbar_wait(bars + B_EPOCH, 0);
      asm volatile("ld.shared.u32 %0, [%1];" : "=r"(epoch) : "r"(bars + B_EPOCHV) : "memory");
      epi_bu(acc0, acc1, cp, sbase, G, rb, cw, epoch);
      TSTAMP(4 + 12 * cw);
    }
#pragma unroll 1
    for (int step = 0; step < 3; step++) {
      const int it0 = cw ? 48 : (step == 0 ? 32 : (step == 1 ? 64 : 112));
      mainloop<1>(acc0, acc1, it0, 16, sbase, cw, cw ? 1 : (step & 1));
      TSTAMP(step == 0 ? 5 + 12 * cw : (step == 1 ? 7 : 9));
      if (step == 2) {
        store_tile<false>(acc0, acc1, sbase + w * 16 * OST, prm, rb, g);
        TSTAMP(10);
        break;
      }
      mbar_wait(bars + B_WPHI, 0);
      mbar_wait(bars + B_EBF, cw ^ 1);
      epi_attn(acc0, acc1, sbase, cw, step == 1);
      TSTAMP(step == 0 ? 6 + 12 * cw : 8);
      if (cw == 1) break;
    }
    if (cw == 1) {
      mainloop<2>(acc0, acc1, 80, 32, sbase, 1, 0);
      TSTAMP(19);
      mbar_wait(bars + B_EBF, 0);
      store_tile<true>(acc0, acc1, sbase + OFF_EB + w * 16 * OST, prm, rb, g);
      TSTAMP(20);
    }
    asm volatile("barrier.cluster.arrive.relaxed.aligned;\nbarrier.cluster.wait.aligned;" ::: "memory");
  }
}

typedef CUresult (*PFN_encodeTiled)(CUtensorMap*, CUtensorMapDataType, cuuint32_t, void*, const cuuint64_t*, const cuuint64_t*,
                                    const cuuint32_t*, const cuuint32_t*, CUtensorMapInterleave, CUtensorMapSwizzle,
                                    CUtensorMapL2promotion, CUtensorMapFloatOOBfill);

bool make_tm(PFN_encodeTiled enc, CUtensorMap* tm, const void* base, int rank, const uint64_t* dims, const uint64_t* strides,
             const uint32_t* box, CUtensorMapSwizzle sw) {
  cuuint64_t gd[5], gs[5];
  cuuint32_t bx[5], es[5];
  for (int i = 0; i < rank; i++) { gd[i] = dims[i]; bx[i] = box[i]; es[i] = 1; }
  for (int i = 0; i + 1 < rank; i++) gs[i] = strides[i];
  return enc(tm, CU_TENSOR_MAP_DATA_TYPE_BFLOAT16, rank, const_cast<void*>(base), gd, gs, bx, es, CU_TENSOR_MAP_INTERLEAVE_NONE, sw,
             CU_TENSOR_MAP_L2_PROMOTION_L2_256B, CU_TENSOR_MAP_FLOAT_OOB_FILL_NONE) == CUDA_SUCCESS;
}
bool make_tm2(PFN_encodeTiled enc, CUtensorMap* tm, const void* base, uint64_t inner, uint64_t outer, uint32_t b0, uint32_t b1,
              CUtensorMapSwizzle sw = CU_TENSOR_MAP_SWIZZLE_128B) {
  const uint64_t dims[2] = {inner, outer}, str[1] = {inner * 2};
  const uint32_t box[2] = {b0, b1};
  return make_tm(enc, tm, base, 2, dims, str, box, sw);
}

}

extern "C" void kernel_launch(void* const* d_in, const int* in_sizes, int n_in, void* d_out, int out_size) {
  (void)in_sizes; (void)n_in; (void)out_size;
  static PFN_encodeTiled enc = nullptr;
  static void *pHT = nullptr, *pO = nullptr;
  if (!enc) {
    void* fn = nullptr;
    cudaDriverEntryPointQueryResult qr;
    if (cudaGetDriverEntryPoint("cuTensorMapEncodeTiled", &fn, cudaEnableDefault, &qr) != cudaSuccess || !fn) return;
    enc = (PFN_encodeTiled)fn;
    cudaFuncSetAttribute(fused_kernel, cudaFuncAttributeMaxDynamicSharedMemorySize, SMEM_BYTES);
    cudaGetSymbolAddress(&pHT, g_HT);
    cudaGetSymbolAddress(&pO, g_O);
  }
  Params prm;
  bool ok = true;
  {
    const uint64_t dims[5] = {1024, 2, 4, 16, 16}, str[4] = {2048, 65536, 4096, 262144};
    const uint32_t box[5] = {64, 2, 4, 16, 1};
    ok &= make_tm(enc, &prm.tmXB, d_in[4], 5, dims, str, box, CU_TENSOR_MAP_SWIZZLE_128B);
  }
  ok &= make_tm2(enc, &prm.tmBre, d_in[7], 1024, 1024, 64, 64);
  ok &= make_tm2(enc, &prm.tmBim, d_in[8], 1024, 1024, 64, 64);
  ok &= make_tm2(enc, &prm.tmXA, d_in[0], 1024, 2048, 64, 128);
  ok &= make_tm2(enc, &prm.tmWqkv, d_in[1], 3072, 1024, 64, 64);
  ok &= make_tm2(enc, &prm.tmWphi, d_in[2], 32, 1024, 32, 64, CU_TENSOR_MAP_SWIZZLE_64B);
  {
    const uint64_t dims[3] = {64, 2048, 32}, str[2] = {4096, 128};
    const uint32_t box[3] = {64, 64, 2};
    ok &= make_tm(enc, &prm.tmHT, pHT, 3, dims, str, box, CU_TENSOR_MAP_SWIZZLE_128B);
  }
  ok &= make_tm2(enc, &prm.tmCre, d_in[9], 1024, 1024, 64, 64);
  ok &= make_tm2(enc, &prm.tmCim, d_in[10], 1024, 1024, 64, 64);
  ok &= make_tm2(enc, &prm.tmO, pO, 1024, 2048, 64, 128);
  ok &= make_tm2(enc, &prm.tmWo, d_in[3], 1024, 1024, 64, 64);
  if (!ok) return;
  prm.xB = (const __nv_bfloat16*)d_in[4];
  prm.lam_re = (const __nv_bfloat16*)d_in[5];
  prm.lam_im = (const __nv_bfloat16*)d_in[6];
  prm.log_dt = (const __nv_bfloat16*)d_in[11];
  prm.dskip = (const __nv_bfloat16*)d_in[12];
  prm.out = (float*)d_out;

  cudaLaunchConfig_t cfg = {};
  cfg.gridDim = dim3(128);
  cfg.blockDim = dim3(384);
  cfg.dynamicSmemBytes = SMEM_BYTES;
  cfg.stream = cudaStreamPerThread;
  cudaLaunchAttribute attr[1];
  attr[0].id = cudaLaunchAttributeClusterDimension;
  attr[0].val.clusterDim.x = 2; attr[0].val.clusterDim.y = 1; attr[0].val.clusterDim.z = 1;
  cfg.attrs = attr;
  cfg.numAttrs = 1;
  cudaLaunchKernelEx(&cfg, fused_kernel, prm);
}
```

```cpp
#include <cuda_runtime.h>
#include <cuda_bf16.h>
#include <cuda.h>
#include <stdint.h>
#include <type_traits>

namespace {

constexpr int SEQ = 2048;
constexpr int DM = 1024;
#define NSTAGES 5
constexpr int STAGES = NSTAGES;
constexpr int STAGE_BYTES = 32768;
constexpr int OFF_EB = 5 * STAGE_BYTES;
constexpr int OFF_PHI = OFF_EB;
constexpr int OFF_V = OFF_EB + 32768;
constexpr int OFF_WPHI = OFF_EB + 53248;
constexpr int OFF_ONES = OFF_EB + 61440;
constexpr int OFF_BAR = OFF_EB + 62464;
constexpr int SMEM_BYTES = OFF_BAR + 256 + 1024;
constexpr int B_EMPTY = 64, B_ORD = 128, B_EBF = 144, B_WPHI = 152, B_EPOCH = 160, B_KVX = 168  , B_EBA = 184, B_EPOCHV = 192, B_DEAD = 196, B_JOB = 200  , B_PARAM = 248;

constexpr int KVW = 40;

struct Params {
  CUtensorMap tmXB;
  CUtensorMap tmBre, tmBim;
  CUtensorMap tmXA;
  CUtensorMap tmWqkv;
  CUtensorMap tmWphi;
  CUtensorMap tmHT;
  CUtensorMap tmCre, tmCim;
  CUtensorMap tmO;
  CUtensorMap tmWo;
  const __nv_bfloat16* xB;
  const __nv_bfloat16* lam_re;
  const __nv_bfloat16* lam_im;
  const __nv_bfloat16* log_dt;
  const __nv_bfloat16* dskip;
  float* out;
};

__device__ __nv_bfloat16 g_HT[2048 * 2048];
__device__ __nv_bfloat16 g_O[SEQ * DM];
__device__ float g_kv[32 * 64 * KVW];
__device__ uint4 g_E[16 * 16 * 64];
struct Flags {
  unsigned ticket;   unsigned pad0[31];
  unsigned zero_cnt; unsigned pad1[31];
  unsigned hcnt[16 * 8];
  unsigned kvcnt[16 * 8];
  unsigned ocnt[2 * 16 * 8];
};
__device__ Flags g_flags;
#define TSTAMP(i)
#define QT(i)

__device__ __forceinline__ uint32_t smem_u32(const void* p) { return (uint32_t)__cvta_generic_to_shared(p); }
__device__ __forceinline__ void mbar_init(uint32_t bar, uint32_t count) {
  asm volatile("mbarrier.init.shared::cta.b64 [%0], %1;" ::"r"(bar), "r"(count));
}
__device__ __forceinline__ void mbar_expect_tx(uint32_t bar, uint32_t bytes) {
  asm volatile("mbarrier.arrive.expect_tx.shared::cta.b64 _, [%0], %1;" ::"r"(bar), "r"(bytes) : "memory");
}
__device__ __forceinline__ void mbar_arrive(uint32_t bar) {
  asm volatile("mbarrier.arrive.shared::cta.b64 _, [%0];" ::"r"(bar) : "memory");
}
__device__ __forceinline__ void mbar_arrive_cluster(uint32_t bar, uint32_t cta) {
  asm volatile("{\n.reg .b32 ra;\nmapa.shared::cluster.u32 ra, %0, %1;\nmbarrier.arrive.shared::cluster.b64 _, [ra];\n}" ::"r"(bar), "r"(cta) : "memory");
}
__device__ __forceinline__ uint32_t dead_addr(uint32_t bar) { return (bar & ~0xFFu) + B_DEAD; }
__device__ __forceinline__ void mbar_wait(uint32_t bar, uint32_t parity) {
  asm volatile(
      "{\n.reg .pred p;\n.reg .u32 c, d;\n"
      "mov.u32 c, 0;\n"
      "WAIT_LOOP:\n"
      "mbarrier.try_wait.parity.shared::cta.b64 p, [%0], %1;\n"
      "@p bra WAIT_DONE;\n"
      "add.u32 c, c, 1;\n"
      "setp.gt.u32 p, c, 0x200000;\n"
      "@p st.volatile.shared.u32 [%2], c;\n"
      "ld.volatile.shared.u32 d, [%2];\n"
      "setp.eq.u32 p, d, 0;\n"
      "@p bra WAIT_LOOP;\n"
      "WAIT_DONE:\n}\n" ::"r"(bar), "r"(parity), "r"(dead_addr(bar)) : "memory");
}
__device__ __forceinline__ bool give_up(uint32_t bars, unsigned spins) {
  unsigned d;
  if (spins > (1u << 20)) asm volatile("st.volatile.shared.u32 [%0], %1;" ::"r"(bars + B_DEAD), "r"(spins) : "memory");
  asm volatile("ld.volatile.shared.u32 %0, [%1];" : "=r"(d) : "r"(bars + B_DEAD) : "memory");
  return d != 0;
}
__device__ __forceinline__ unsigned ld_relaxed(const unsigned* p) {
  unsigned v;
  asm volatile("ld.relaxed.gpu.global.u32 %0, [%1];" : "=r"(v) : "l"(p) : "memory");
  return v;
}
__device__ __forceinline__ void wait_ge(uint32_t bars, const unsigned* p, unsigned target) {
  unsigned spins = 0;
  while ((int)(ld_relaxed(p) - target) < 0) {
    __nanosleep(128);
    if (give_up(bars, ++spins)) break;
  }
}
__device__ __forceinline__ void red_release_add(unsigned* p, unsigned v) {
  asm volatile("red.release.gpu.global.add.u32 [%0], %1;" ::"l"(p), "r"(v) : "memory");
}
__device__ __forceinline__ void red_relaxed_add(unsigned* p, unsigned v) {
  asm volatile("red.relaxed.gpu.global.add.u32 [%0], %1;" ::"l"(p), "r"(v) : "memory");
}
__device__ __forceinline__ void st_tagged(uint4* p, float a, float b, unsigned tag) {
  const unsigned long long w0 = ((unsigned long long)tag << 32) | __float_as_uint(a);
  const unsigned long long w1 = ((unsigned long long)tag << 32) | __float_as_uint(b);
  asm volatile("st.relaxed.gpu.global.v2.b64 [%0], {%1, %2};" ::"l"(p), "l"(w0), "l"(w1) : "memory");
}
__device__ __forceinline__ void bulk_commit() { asm volatile("cp.async.bulk.commit_group;" ::: "memory"); }
__device__ __forceinline__ void bulk_wait_read() { asm volatile("cp.async.bulk.wait_group.read 0;" ::: "memory"); }
__device__ __forceinline__ void bulk_wait_all() { asm volatile("cp.async.bulk.wait_group 0;" ::: "memory"); }
__device__ __forceinline__ void bulk_reduce_f32(float* dst, uint32_t src, uint32_t bytes) {
  asm volatile("cp.reduce.async.bulk.global.shared::cta.bulk_group.add.f32 [%0], [%1], %2;" ::"l"(dst), "r"(src), "r"(bytes) : "memory");
}
__device__ __forceinline__ void tma_store_3d(const CUtensorMap* tm, uint32_t src, int c0, int c1, int c2) {
  asm volatile("cp.async.bulk.tensor.3d.global.shared::cta.bulk_group [%0, {%2, %3, %4}], [%1];"
               ::"l"(tm), "r"(src), "r"(c0), "r"(c1), "r"(c2) : "memory");
}
__device__ __forceinline__ void fence_async_smem() { asm volatile("fence.proxy.async.shared::cta;" ::: "memory"); }
__device__ __forceinline__ void tma_2d(uint32_t dst, const CUtensorMap* tm, int c0, int c1, uint32_t bar) {
  asm volatile("cp.async.bulk.tensor.2d.shared::cluster.global.mbarrier::complete_tx::bytes [%0], [%1, {%3, %4}], [%2];"
               ::"r"(dst), "l"(tm), "r"(bar), "r"(c0), "r"(c1) : "memory");
}
__device__ __forceinline__ void tma_3d(uint32_t dst, const CUtensorMap* tm, int c0, int c1, int c2, uint32_t bar) {
  asm volatile("cp.async.bulk.tensor.3d.shared::cluster.global.mbarrier::complete_tx::bytes [%0], [%1, {%3, %4, %5}], [%2];"
               ::"r"(dst), "l"(tm), "r"(bar), "r"(c0), "r"(c1), "r"(c2) : "memory");
}
__device__ __forceinline__ void tma_5d(uint32_t dst, const CUtensorMap* tm, int c0, int c1, int c2, int c3, int c4, uint32_t bar) {
  asm volatile("cp.async.bulk.tensor.5d.shared::cluster.global.mbarrier::complete_tx::bytes [%0], [%1, {%3, %4, %5, %6, %7}], [%2];"
               ::"r"(dst), "l"(tm), "r"(bar), "r"(c0), "r"(c1), "r"(c2), "r"(c3), "r"(c4) : "memory");
}
__device__ __forceinline__ void tma_2d_mc(uint32_t dst, const CUtensorMap* tm, int c0, int c1, uint32_t bar) {
  asm volatile("cp.async.bulk.tensor.2d.shared::cluster.global.mbarrier::complete_tx::bytes.multicast::cluster [%0], [%1, {%3, %4}], [%2], %5;"
               ::"r"(dst), "l"(tm), "r"(bar), "r"(c0), "r"(c1), "h"((uint16_t)3) : "memory");
}
__device__ __forceinline__ void tma_store_2d(const CUtensorMap* tm, uint32_t src, int c0, int c1) {
  asm volatile("cp.async.bulk.tensor.2d.global.shared::cta.bulk_group [%0, {%2, %3}], [%1];"
               ::"l"(tm), "r"(src), "r"(c0), "r"(c1) : "memory");
}
__device__ __forceinline__ bool elect_one() {
  uint32_t p;
  asm volatile("{\n.reg .pred e;\nelect.sync _|e, 0xffffffff;\nselp.u32 %0, 1, 0, e;\n}" : "=r"(p));
  return p != 0;
}
__device__ __forceinline__ void prefetch_tm(const CUtensorMap* tm) {
  asm volatile("prefetch.tensormap [%0];" ::"l"(tm) : "memory");
}
__device__ __forceinline__ void wgmma_fence() { asm volatile("wgmma.fence.sync.aligned;" ::: "memory"); }
__device__ __forceinline__ void wgmma_commit() { asm volatile("wgmma.commit_group.sync.aligned;" ::: "memory"); }
template <int N> __device__ __forceinline__ void wgmma_wait() { asm volatile("wgmma.wait_group.sync.aligned %0;" ::"n"(N) : "memory"); }
__device__ __forceinline__ void wg_bar(int id) {
  if (id == 1) asm volatile("bar.sync 1, 128;" ::: "memory");
  else asm volatile("bar.sync 2, 128;" ::: "memory");
}
template <int R> __device__ __forceinline__ void reg_alloc() { asm volatile("setmaxnreg.inc.sync.aligned.u32 %0;" ::"n"(R)); }
template <int R> __device__ __forceinline__ void reg_dealloc() { asm volatile("setmaxnreg.dec.sync.aligned.u32 %0;" ::"n"(R)); }

__device__ __forceinline__ uint64_t make_desc(uint32_t saddr, uint32_t lbo_bytes, uint32_t sbo_bytes, uint32_t layout) {
  uint64_t d = (uint64_t)((saddr & 0x3FFFF) >> 4);
  d |= (uint64_t)((lbo_bytes & 0x3FFFF) >> 4) << 16;
  d |= (uint64_t)((sbo_bytes & 0x3FFFF) >> 4) << 32;
  d |= (uint64_t)layout << 62;
  return d;
}
__device__ __forceinline__ uint64_t desc128(uint32_t lo) { return ((uint64_t)0x40000040u << 32) | lo; }
__device__ __forceinline__ uint32_t pack_bf16(float lo, float hi) {
  uint32_t r;
  asm("cvt.rn.bf16x2.f32 %0, %1, %2;" : "=r"(r) : "f"(hi), "f"(lo));
  return r;
}
__device__ __forceinline__ float ex2(float x) { float y; asm("ex2.approx.ftz.f32 %0, %1;" : "=f"(y) : "f"(x)); return y; }
__device__ __forceinline__ float rcp(float x) { float y; asm("rcp.approx.ftz.f32 %0, %1;" : "=f"(y) : "f"(x)); return y; }
__device__ __forceinline__ void stmatrix_x4(uint32_t addr, uint32_t r0, uint32_t r1, uint32_t r2, uint32_t r3) {
  asm volatile("stmatrix.sync.aligned.m8n8.x4.shared.b16 [%0], {%1, %2, %3, %4};" ::"r"(addr), "r"(r0), "r"(r1), "r"(r2), "r"(r3) : "memory");
}
template <int N> __device__ __forceinline__ void fence_regs(float (&d)[N]) {
#pragma unroll
  for (int i = 0; i < N; i++) asm volatile("" : "+f"(d[i])::"memory");
}

template <int TA, int TB>
__device__ __forceinline__ void wgmma_m64n128k16_ss(float (&d)[64], uint64_t descA, uint64_t descB) {
  asm volatile("{\n.reg .pred p;\nsetp.ne.b32 p, 1, 0;\n"
    "wgmma.mma_async.sync.aligned.m64n128k16.f32.bf16.bf16 "
    "{%0, %1, %2, %3, %4, %5, %6, %7, %8, %9, %10, %11, %12, %13, %14, %15, %16, %17, %18, %19, %20, %21, %22, %23, %24, %25, %26, %27, %28, %29, %30, %31, %32, %33, %34, %35, %36, %37, %38, %39, %40, %41, %42, %43, %44, %45, %46, %47, %48, %49, %50, %51, %52, %53, %54, %55, %56, %57, %58, %59, %60, %61, %62, %63}, "
    "%64, %65, p, 1, 1, %66, %67;\n}\n"
    : "+f"(d[0]), "+f"(d[1]), "+f"(d[2]), "+f"(d[3]), "+f"(d[4]), "+f"(d[5]), "+f"(d[6]), "+f"(d[7]), "+f"(d[8]), "+f"(d[9]), "+f"(d[10]), "+f"(d[11]), "+f"(d[12]), "+f"(d[13]), "+f"(d[14]), "+f"(d[15]), "+f"(d[16]), "+f"(d[17]), "+f"(d[18]), "+f"(d[19]), "+f"(d[20]), "+f"(d[21]), "+f"(d[22]), "+f"(d[23]), "+f"(d[24]), "+f"(d[25]), "+f"(d[26]), "+f"(d[27]), "+f"(d[28]), "+f"(d[29]), "+f"(d[30]), "+f"(d[31]), "+f"(d[32]), "+f"(d[33]), "+f"(d[34]), "+f"(d[35]), "+f"(d[36]), "+f"(d[37]), "+f"(d[38]), "+f"(d[39]), "+f"(d[40]), "+f"(d[41]), "+f"(d[42]), "+f"(d[43]), "+f"(d[44]), "+f"(d[45]), "+f"(d[46]), "+f"(d[47]), "+f"(d[48]), "+f"(d[49]), "+f"(d[50]), "+f"(d[51]), "+f"(d[52]), "+f"(d[53]), "+f"(d[54]), "+f"(d[55]), "+f"(d[56]), "+f"(d[57]), "+f"(d[58]), "+f"(d[59]), "+f"(d[60]), "+f"(d[61]), "+f"(d[62]), "+f"(d[63])
    : "l"(descA), "l"(descB), "n"(TA), "n"(TB));
}

template <int TA, int TB>
__device__ __forceinline__ void wgmma_m64n32k16_ss(float (&d)[16], uint64_t descA, uint64_t descB) {
  asm volatile("{\n.reg .pred p;\nsetp.ne.b32 p, 1, 0;\n"
    "wgmma.mma_async.sync.aligned.m64n32k16.f32.bf16.bf16 "
    "{%0, %1, %2, %3, %4, %5, %6, %7, %8, %9, %10, %11, %12, %13, %14, %15}, "
    "%16, %17, p, 1, 1, %18, %19;\n}\n"
    : "+f"(d[0]), "+f"(d[1]), "+f"(d[2]), "+f"(d[3]), "+f"(d[4]), "+f"(d[5]), "+f"(d[6]), "+f"(d[7]), "+f"(d[8]), "+f"(d[9]), "+f"(d[10]), "+f"(d[11]), "+f"(d[12]), "+f"(d[13]), "+f"(d[14]), "+f"(d[15])
    : "l"(descA), "l"(descB), "n"(TA), "n"(TB));
}

template <int TA, int TB>
__device__ __forceinline__ void wgmma_m64n32k16_ss_init(float (&d)[16], uint64_t descA, uint64_t descB) {
  asm volatile("{\n.reg .pred p;\nsetp.ne.b32 p, 0, 0;\n"
    "wgmma.mma_async.sync.aligned.m64n32k16.f32.bf16.bf16 "
    "{%0, %1, %2, %3, %4, %5, %6, %7, %8, %9, %10, %11, %12, %13, %14, %15}, "
    "%16, %17, p, 1, 1, %18, %19;\n}\n"
    : "=f"(d[0]), "=f"(d[1]), "=f"(d[2]), "=f"(d[3]), "=f"(d[4]), "=f"(d[5]), "=f"(d[6]), "=f"(d[7]), "=f"(d[8]), "=f"(d[9]), "=f"(d[10]), "=f"(d[11]), "=f"(d[12]), "=f"(d[13]), "=f"(d[14]), "=f"(d[15])
    : "l"(descA), "l"(descB), "n"(TA), "n"(TB));
}

template <int TA, int TB>
__device__ __forceinline__ void wgmma_m64n40k16_ss(float (&d)[20], uint64_t descA, uint64_t descB) {
  asm volatile("{\n.reg .pred p;\nsetp.ne.b32 p, 1, 0;\n"
    "wgmma.mma_async.sync.aligned.m64n40k16.f32.bf16.bf16 "
    "{%0, %1, %2, %3, %4, %5, %6, %7, %8, %9, %10, %11, %12, %13, %14, %15, %16, %17, %18, %19}, "
    "%20, %21, p, 1, 1, %22, %23;\n}\n"
    : "+f"(d[0]), "+f"(d[1]), "+f"(d[2]), "+f"(d[3]), "+f"(d[4]), "+f"(d[5]), "+f"(d[6]), "+f"(d[7]), "+f"(d[8]), "+f"(d[9]), "+f"(d[10]), "+f"(d[11]), "+f"(d[12]), "+f"(d[13]), "+f"(d[14]), "+f"(d[15]), "+f"(d[16]), "+f"(d[17]), "+f"(d[18]), "+f"(d[19])
    : "l"(descA), "l"(descB), "n"(TA), "n"(TB));
}

template <int TA, int TB>
__device__ __forceinline__ void wgmma_m64n40k16_ss_init(float (&d)[20], uint64_t descA, uint64_t descB) {
  asm volatile("{\n.reg .pred p;\nsetp.ne.b32 p, 0, 0;\n"
    "wgmma.mma_async.sync.aligned.m64n40k16.f32.bf16.bf16 "
    "{%0, %1, %2, %3, %4, %5, %6, %7, %8, %9, %10, %11, %12, %13, %14, %15, %16, %17, %18, %19}, "
    "%20, %21, p, 1, 1, %22, %23;\n}\n"
    : "=f"(d[0]), "=f"(d[1]), "=f"(d[2]), "=f"(d[3]), "=f"(d[4]), "=f"(d[5]), "=f"(d[6]), "=f"(d[7]), "=f"(d[8]), "=f"(d[9]), "=f"(d[10]), "=f"(d[11]), "=f"(d[12]), "=f"(d[13]), "=f"(d[14]), "=f"(d[15]), "=f"(d[16]), "=f"(d[17]), "=f"(d[18]), "=f"(d[19])
    : "l"(descA), "l"(descB), "n"(TA), "n"(TB));
}

template <int TB>
__device__ __forceinline__ void wgmma_m64n40k16_rs(float (&d)[20], uint32_t a0, uint32_t a1, uint32_t a2, uint32_t a3, uint64_t descB) {
  asm volatile("{\n.reg .pred p;\nsetp.ne.b32 p, 1, 0;\n"
    "wgmma.mma_async.sync.aligned.m64n40k16.f32.bf16.bf16 "
    "{%0, %1, %2, %3, %4, %5, %6, %7, %8, %9, %10, %11, %12, %13, %14, %15, %16, %17, %18, %19}, "
    "{%20, %21, %22, %23}, %24, p, 1, 1, %25;\n}\n"
    : "+f"(d[0]), "+f"(d[1]), "+f"(d[2]), "+f"(d[3]), "+f"(d[4]), "+f"(d[5]), "+f"(d[6]), "+f"(d[7]), "+f"(d[8]), "+f"(d[9]), "+f"(d[10]), "+f"(d[11]), "+f"(d[12]), "+f"(d[13]), "+f"(d[14]), "+f"(d[15]), "+f"(d[16]), "+f"(d[17]), "+f"(d[18]), "+f"(d[19])
    : "r"(a0), "r"(a1), "r"(a2), "r"(a3), "l"(descB), "n"(TB));
}

template <int TB>
__device__ __forceinline__ void wgmma_m64n40k16_rs_init(float (&d)[20], uint32_t a0, uint32_t a1, uint32_t a2, uint32_t a3, uint64_t descB) {
  asm volatile("{\n.reg .pred p;\nsetp.ne.b32 p, 0, 0;\n"
    "wgmma.mma_async.sync.aligned.m64n40k16.f32.bf16.bf16 "
    "{%0, %1, %2, %3, %4, %5, %6, %7, %8, %9, %10, %11, %12, %13, %14, %15, %16, %17, %18, %19}, "
    "{%20, %21, %22, %23}, %24, p, 1, 1, %25;\n}\n"
    : "=f"(d[0]), "=f"(d[1]), "=f"(d[2]), "=f"(d[3]), "=f"(d[4]), "=f"(d[5]), "=f"(d[6]), "=f"(d[7]), "=f"(d[8]), "=f"(d[9]), "=f"(d[10]), "=f"(d[11]), "=f"(d[12]), "=f"(d[13]), "=f"(d[14]), "=f"(d[15]), "=f"(d[16]), "=f"(d[17]), "=f"(d[18]), "=f"(d[19])
    : "r"(a0), "r"(a1), "r"(a2), "r"(a3), "l"(descB), "n"(TB));
}

template <int MODE>
__device__ __forceinline__ void mainloop(float (&acc0)[64], float (&acc1)[64], int it0, int nkb, uint32_t sbase, int cw,
                                         uint32_t ord_parity) {
  const uint32_t bars = sbase + OFF_BAR;
  const int lane = threadIdx.x & 31;
  int stage = it0 % STAGES;
  uint32_t phase = (it0 / STAGES) & 1;
#pragma unroll
  for (int i = 0; i < 64; i++) { acc0[i] = 0.f; acc1[i] = 0.f; }
  mbar_wait(bars + B_ORD + 8 * cw, ord_parity);
  int prev = 0;
  for (int kb = 0; kb < nkb; kb++) {
    mbar_wait(bars + 8 * stage, phase);
    if (kb == nkb - 1 && (threadIdx.x & 127) == 0) mbar_arrive(bars + B_ORD + 8 * (cw ^ 1));
    const uint32_t lo = ((sbase & 0x3FFFFu) + stage * STAGE_BYTES) >> 4;
    const uint32_t loK = lo | (1u << 16), loM = lo | (512u << 16);
    wgmma_fence();
#pragma unroll
    for (int k = 0; k < 4; k++) {
      if (MODE == 0) {
        const uint64_t dx = desc128(loK + 1024 + 2 * k);
        wgmma_m64n128k16_ss<0, 0>(acc0, desc128(loK + 2 * k), dx);
        wgmma_m64n128k16_ss<0, 0>(acc1, desc128(loK + 512 + 2 * k), dx);
      } else if (MODE == 1) {
        const uint64_t dw = desc128(loM + 128 * k);
        wgmma_m64n128k16_ss<0, 1>(acc0, desc128(loK + 1024 + 2 * k), dw);
        wgmma_m64n128k16_ss<0, 1>(acc1, desc128(loK + 1536 + 2 * k), dw);
      } else {
        const uint64_t dw = desc128(loK + 2 * k);
        wgmma_m64n128k16_ss<1, 0>(acc0, desc128(loM + 1024 + 128 * k), dw);
        wgmma_m64n128k16_ss<1, 0>(acc1, desc128(loM + 1536 + 128 * k), dw);
      }
    }
    wgmma_commit();
    wgmma_wait<1>();
    if (kb > 0 && lane < 2) mbar_arrive_cluster(bars + B_EMPTY + 8 * prev, lane);
    prev = stage;
    if (++stage == STAGES) { stage = 0; phase ^= 1; }
  }
  wgmma_wait<0>();
  if (lane < 2) mbar_arrive_cluster(bars + B_EMPTY + 8 * prev, lane);
  fence_regs(acc0);
  fence_regs(acc1);
}

template <int N>
__device__ __forceinline__ void dual_softmax_n(const float (&p)[N][16], uint32_t (&pos)[N][8], uint32_t (&neg)[N][8]) {
  constexpr float L2E = 1.4426950408889634f;
  float ca[N][2], cb[N][2];
  {
    float mx[N][2], mn[N][2];
#pragma unroll
    for (int i = 0; i < N; i++)
#pragma unroll
      for (int r = 0; r < 2; r++) {
        const int o = 2 * r;
        mx[i][r] = fmaxf(fmaxf(fmaxf(p[i][o], p[i][o + 1]), fmaxf(p[i][4 + o], p[i][5 + o])),
                         fmaxf(fmaxf(p[i][8 + o], p[i][9 + o]), fmaxf(p[i][12 + o], p[i][13 + o])));
        mn[i][r] = fminf(fminf(fminf(p[i][o], p[i][o + 1]), fminf(p[i][4 + o], p[i][5 + o])),
                         fminf(fminf(p[i][8 + o], p[i][9 + o]), fminf(p[i][12 + o], p[i][13 + o])));
      }
#pragma unroll
    for (int o = 1; o <= 2; o <<= 1) {
      float tx[N][2], tn[N][2];
#pragma unroll
      for (int i = 0; i < N; i++)
#pragma unroll
        for (int r = 0; r < 2; r++) { tx[i][r] = __shfl_xor_sync(0xffffffffu, mx[i][r], o); tn[i][r] = __shfl_xor_sync(0xffffffffu, mn[i][r], o); }
#pragma unroll
      for (int i = 0; i < N; i++)
#pragma unroll
        for (int r = 0; r < 2; r++) { mx[i][r] = fmaxf(mx[i][r], tx[i][r]); mn[i][r] = fminf(mn[i][r], tn[i][r]); }
    }
#pragma unroll
    for (int i = 0; i < N; i++)
#pragma unroll
      for (int r = 0; r < 2; r++) { ca[i][r] = -mx[i][r] * L2E; cb[i][r] = mn[i][r] * L2E; }
  }
  float ep[2][16], en[2][16];
  float rp[2], rn[2];
#pragma unroll
  for (int i = 0; i <= N; i++) {
    const int cur = i & 1, prv = cur ^ 1;
    if (i > 0) {
      float sp[2], sn[2];
#pragma unroll
      for (int r = 0; r < 2; r++) {
        const int o = 2 * r;
        sp[r] = ((ep[prv][o] + ep[prv][o + 1]) + (ep[prv][4 + o] + ep[prv][5 + o])) + ((ep[prv][8 + o] + ep[prv][9 + o]) + (ep[prv][12 + o] + ep[prv][13 + o]));
        sn[r] = ((en[prv][o] + en[prv][o + 1]) + (en[prv][4 + o] + en[prv][5 + o])) + ((en[prv][8 + o] + en[prv][9 + o]) + (en[prv][12 + o] + en[prv][13 + o]));
      }
      float t0[2], t1[2];
#pragma unroll
      for (int r = 0; r < 2; r++) { t0[r] = __shfl_xor_sync(0xffffffffu, sp[r], 1); t1[r] = __shfl_xor_sync(0xffffffffu, sn[r], 1); }
      if (i < N) {
#pragma unroll
        for (int e = 0; e < 4; e++) {
          ep[cur][e] = ex2(fmaf(p[i][e], L2E, ca[i][e >> 1])); en[cur][e] = ex2(fmaf(p[i][e], -L2E, cb[i][e >> 1]));
        }
      }
#pragma unroll
      for (int r = 0; r < 2; r++) { sp[r] += t0[r]; sn[r] += t1[r]; }
#pragma unroll
      for (int r = 0; r < 2; r++) { t0[r] = __shfl_xor_sync(0xffffffffu, sp[r], 2); t1[r] = __shfl_xor_sync(0xffffffffu, sn[r], 2); }
      if (i < N) {
#pragma unroll
        for (int e = 4; e < 8; e++) {
          ep[cur][e] = ex2(fmaf(p[i][e], L2E, ca[i][(e >> 1) & 1])); en[cur][e] = ex2(fmaf(p[i][e], -L2E, cb[i][(e >> 1) & 1]));
        }
      }
#pragma unroll
      for (int r = 0; r < 2; r++) { rp[r] = rcp(sp[r] + t0[r]); rn[r] = rcp(sn[r] + t1[r]); }
    } else {
#pragma unroll
      for (int e = 0; e < 8; e++) {
        ep[cur][e] = ex2(fmaf(p[i][e], L2E, ca[i][(e >> 1) & 1])); en[cur][e] = ex2(fmaf(p[i][e], -L2E, cb[i][(e >> 1) & 1]));
      }
    }
#pragma unroll
    for (int j = 0; j < 4; j++) {
      if (i < N && j >= 2) {
#pragma unroll
        for (int e = 4 * j; e < 4 * j + 4; e++) {
          ep[cur][e] = ex2(fmaf(p[i][e], L2E, ca[i][(e >> 1) & 1])); en[cur][e] = ex2(fmaf(p[i][e], -L2E, cb[i][(e >> 1) & 1]));
        }
      }
      if (i > 0) {
#pragma unroll
        for (int r = 0; r < 2; r++) {
          pos[i - 1][2 * j + r] = pack_bf16(ep[prv][4 * j + 2 * r] * rp[r], ep[prv][4 * j + 2 * r + 1] * rp[r]);
          neg[i - 1][2 * j + r] = pack_bf16(en[prv][4 * j + 2 * r] * rn[r], en[prv][4 * j + 2 * r + 1] * rn[r]);
        }
      }
    }
  }
}

struct cplx { float r, i; };
__device__ __forceinline__ cplx cmul(cplx a, cplx b) { return {a.r * b.r - a.i * b.i, a.r * b.i + a.i * b.r}; }
__device__ __forceinline__ cplx cfma(cplx a, cplx b, cplx c) {
  return {fmaf(a.r, b.r, fmaf(-a.i, b.i, c.r)), fmaf(a.r, b.i, fmaf(a.i, b.r, c.i))};
}
__device__ __forceinline__ cplx shfl_up_c(cplx v, int d) {
  return {__shfl_up_sync(0xffffffffu, v.r, d, 4), __shfl_up_sync(0xffffffffu, v.i, d, 4)};
}

struct ChanParams { cplx lam, c2; };

__device__ __forceinline__ ChanParams chan_params(float lr, float li, float log_dt) {
  const float dt = __bfloat162float(__float2bfloat16(expf(log_dt)));
  const float mag = expf(dt * lr);
  float sn, cs;
  sincosf(dt * li, &sn, &cs);
  ChanParams c;
  c.lam = {mag * cs, mag * sn};
  const float nr = c.lam.r - 1.0f, ni = c.lam.i;
  const float den = lr * lr + li * li;
  c.c2 = {2.0f * (nr * lr + ni * li) / den, 2.0f * (ni * lr - nr * li) / den};
  return c;
}

__device__ __forceinline__ void epi_bu(float (&are)[64], float (&aim)[64], const ChanParams (&cp)[2],
                                       uint32_t sbase, int G, int chunk, int cw, unsigned epoch) {
  const int lane = threadIdx.x & 31, w = (threadIdx.x & 127) >> 5, q = lane & 3, r8 = lane >> 2;
  cplx E[2] = {{0.f, 0.f}, {0.f, 0.f}};
#pragma unroll
  for (int k8 = 0; k8 < 16; k8++)
#pragma unroll
    for (int e = 0; e < 2; e++)
#pragma unroll
      for (int c = 0; c < 2; c++) E[c] = cfma(cp[c].lam, E[c], cplx{are[4 * k8 + 2 * c + e], aim[4 * k8 + 2 * c + e]});
  TSTAMP(32 + 4 * (threadIdx.x >> 8));
  cplx L32[2], L128[2], prev[2];
#pragma unroll
  for (int c = 0; c < 2; c++) {
    cplx l = cp[c].lam;
#pragma unroll
    for (int s = 0; s < 5; s++) l = cmul(l, l);
    L32[c] = l;
    const cplx l64 = cmul(l, l);
    L128[c] = cmul(l64, l64);
    cplx t = shfl_up_c(E[c], 1);
    if (q >= 1) E[c] = cfma(L32[c], t, E[c]);
    t = shfl_up_c(E[c], 2);
    if (q >= 2) E[c] = cfma(l64, t, E[c]);
    prev[c] = shfl_up_c(E[c], 1);
    if (q == 0) prev[c] = {0.f, 0.f};
  }
  uint4* gE = g_E + (size_t)G * 16 * 64 + 16 * w + r8;
  if (q == 3) {
    st_tagged(gE + chunk * 64, E[0].r, E[0].i, epoch);
    st_tagged(gE + chunk * 64 + 8, E[1].r, E[1].i, epoch);
  }
  cplx V[2][4];
  {
    unsigned long long w0[8], w1[8];
    unsigned pending = 0;
#pragma unroll
    for (int i = 0; i < 8; i++) {
      w0[i] = 0ull; w1[i] = 0ull;
      if (chunk - 1 - 4 * q - (i & 3) >= 0) pending |= 1u << i;
    }
    unsigned spins = 0;
    if (chunk > 0) __nanosleep(300);
    while (true) {
#pragma unroll
      for (int i = 0; i < 8; i++)
        asm volatile("{\n.reg .pred p;\nsetp.ne.u32 p, %3, 0;\n@p ld.relaxed.gpu.global.v2.b64 {%0, %1}, [%2];\n}"
                     : "+l"(w0[i]), "+l"(w1[i]) : "l"(gE + (chunk - 1 - 4 * q - (i & 3)) * 64 + 8 * (i >> 2)), "r"(pending & (1u << i)) : "memory");
#pragma unroll
      for (int i = 0; i < 8; i++)
        if ((unsigned)(w0[i] >> 32) == epoch && (unsigned)(w1[i] >> 32) == epoch) pending &= ~(1u << i);
      if (__all_sync(0xffffffffu, pending == 0)) break;
      __nanosleep(150);
      if (give_up(sbase + OFF_BAR, ++spins)) break;
    }
#pragma unroll
    for (int i = 0; i < 8; i++) V[i >> 2][i & 3] = {__uint_as_float((unsigned)w0[i]), __uint_as_float((unsigned)w1[i])};
  }
  TSTAMP(33 + 4 * (threadIdx.x >> 8));
  cplx s[2];
#pragma unroll
  for (int c = 0; c < 2; c++) {
    cplx Pq = V[c][3];
#pragma unroll
    for (int jj = 2; jj >= 0; jj--) Pq = cfma(L128[c], Pq, V[c][jj]);
    const cplx l256 = cmul(L128[c], L128[c]);
    const cplx l512 = cmul(l256, l256);
    cplx F = {1.f, 0.f};
    cplx G32 = {1.f, 0.f};
    if (q >= 1) { F = l512; G32 = L32[c]; }
    if (q >= 2) { F = cmul(F, l512); G32 = cmul(G32, L32[c]); }
    if (q >= 3) { F = cmul(F, l512); G32 = cmul(G32, L32[c]); }
    Pq = cmul(Pq, F);
#pragma unroll
    for (int o = 1; o <= 2; o <<= 1) {
      Pq.r += __shfl_xor_sync(0xffffffffu, Pq.r, o);
      Pq.i += __shfl_xor_sync(0xffffffffu, Pq.i, o);
    }
    s[c] = cfma(G32, Pq, prev[c]);
  }
  TSTAMP(34 + 4 * (threadIdx.x >> 8));
  if (cw == 1) mbar_wait(sbase + OFF_BAR + B_EBF, 0);
#pragma unroll
  for (int qq = 0; qq < 4; qq++) {
    uint32_t ore[2][4], oim[2][4];
#pragma unroll
    for (int kk = 0; kk < 4; kk++) {
      const int k8 = 4 * qq + kk;
      float hr[2][2], hi[2][2];
#pragma unroll
      for (int e = 0; e < 2; e++)
#pragma unroll
        for (int c = 0; c < 2; c++) {
          s[c] = cfma(cp[c].lam, s[c], cplx{are[4 * k8 + 2 * c + e], aim[4 * k8 + 2 * c + e]});
          hr[c][e] = fmaf(cp[c].c2.r, s[c].r, -cp[c].c2.i * s[c].i);
          hi[c][e] = -fmaf(cp[c].c2.r, s[c].i, cp[c].c2.i * s[c].r);
        }
#pragma unroll
      for (int c = 0; c < 2; c++) {
        ore[c][kk] = pack_bf16(hr[c][0], hr[c][1]);
        oim[c][kk] = pack_bf16(hi[c][0], hi[c][1]);
      }
    }
#pragma unroll
    for (int c = 0; c < 2; c++) {
      const int row = 16 * w + r8 + 8 * c;
      const uint32_t addr = sbase + OFF_PHI + (qq >> 1) * 8192 + row * 128 + ((((qq & 1) * 4 + q) ^ (row & 7)) << 4);
      asm volatile("st.shared.v4.b32 [%0], {%1, %2, %3, %4};" ::"r"(addr), "r"(ore[c][0]), "r"(ore[c][1]), "r"(ore[c][2]), "r"(ore[c][3]) : "memory");
      asm volatile("st.shared.v4.b32 [%0], {%1, %2, %3, %4};" ::"r"(addr + 16384), "r"(oim[c][0]), "r"(oim[c][1]), "r"(oim[c][2]), "r"(oim[c][3]) : "memory");
    }
  }
  TSTAMP(35 + 4 * (threadIdx.x >> 8));
  fence_async_smem();
  wg_bar(1 + cw);
  if ((threadIdx.x & 127) == 0) mbar_arrive(sbase + OFF_BAR + B_JOB + 8 * cw);
}

__device__ __forceinline__ void q_issue_num(float (&num)[20], const uint32_t (&pos)[8], const uint32_t (&neg)[8], uint32_t b) {
  wgmma_fence();
  wgmma_m64n40k16_rs_init<1>(num, pos[0], pos[1], pos[2], pos[3], make_desc(b, 640, 128, 0));
  wgmma_m64n40k16_rs<1>(num, pos[4], pos[5], pos[6], pos[7], make_desc(b + 1280, 640, 128, 0));
  wgmma_m64n40k16_rs<1>(num, neg[0], neg[1], neg[2], neg[3], make_desc(b + 2560, 640, 128, 0));
  wgmma_m64n40k16_rs<1>(num, neg[4], neg[5], neg[6], neg[7], make_desc(b + 3840, 640, 128, 0));
  wgmma_commit();
}
__device__ __forceinline__ void q_store_o(const float (&num)[20], uint32_t rowaddr, int chunk0) {
  const int lane = threadIdx.x & 31, mi = lane >> 3, rin = lane & 7;
  const float d0 = __shfl_sync(0xffffffffu, num[16], lane & ~3), d1 = __shfl_sync(0xffffffffu, num[18], lane & ~3);
  const float i0 = __fdividef(1.0f, d0 + 1e-6f), i1 = __fdividef(1.0f, d1 + 1e-6f);
#pragma unroll
  for (int jp = 0; jp < 2; jp++) {
    const int c0 = chunk0 + jp * 2 + (mi >> 1);
    stmatrix_x4(rowaddr + ((c0 ^ rin) << 4), pack_bf16(num[8 * jp] * i0, num[8 * jp + 1] * i0),
                pack_bf16(num[8 * jp + 2] * i1, num[8 * jp + 3] * i1), pack_bf16(num[8 * jp + 4] * i0, num[8 * jp + 5] * i0),
                pack_bf16(num[8 * jp + 6] * i1, num[8 * jp + 7] * i1));
  }
}
__device__ __forceinline__ void epi_attn(float (&acc0)[64], float (&acc1)[64], uint32_t sbase, int cw, bool isq) {
  const int t = threadIdx.x & 127, lane = t & 31, w = t >> 5, q = lane & 3, r8 = lane >> 2;
  const int mi = lane >> 3, rin = lane & 7;
  const int row0 = w * 16 + (mi & 1) * 8 + rin;
  {
    const uint32_t tile = sbase + OFF_PHI + (isq ? 0 : 16384) + row0 * 128;
#pragma unroll
    for (int j = 0; j < 8; j += 2) {
      const uint32_t addr = tile + (((j + (mi >> 1)) ^ rin) << 4);
      stmatrix_x4(addr, pack_bf16(acc0[4 * j], acc0[4 * j + 1]), pack_bf16(acc0[4 * j + 2], acc0[4 * j + 3]),
                  pack_bf16(acc0[4 * j + 4], acc0[4 * j + 5]), pack_bf16(acc0[4 * j + 6], acc0[4 * j + 7]));
      stmatrix_x4(addr + 8192, pack_bf16(acc1[4 * j], acc1[4 * j + 1]), pack_bf16(acc1[4 * j + 2], acc1[4 * j + 3]),
                  pack_bf16(acc1[4 * j + 4], acc1[4 * j + 5]), pack_bf16(acc1[4 * j + 6], acc1[4 * j + 7]));
    }
  }
#pragma unroll
  for (int j = 8; j < 16; j += 2) {
    const uint32_t aq = sbase + OFF_PHI + 16384 + row0 * 128 + (((j - 8 + (mi >> 1)) ^ rin) << 4);
    const uint32_t av = sbase + OFF_V + ((j - 8) >> 2) * 8192 + row0 * 64 + ((((j & 3) + (mi >> 1)) ^ ((row0 >> 1) & 3)) << 4);
    const uint32_t addr = isq ? aq : av;
    stmatrix_x4(addr, pack_bf16(acc0[4 * j], acc0[4 * j + 1]), pack_bf16(acc0[4 * j + 2], acc0[4 * j + 3]),
                pack_bf16(acc0[4 * j + 4], acc0[4 * j + 5]), pack_bf16(acc0[4 * j + 6], acc0[4 * j + 7]));
    stmatrix_x4(addr + (isq ? 8192 : 4096), pack_bf16(acc1[4 * j], acc1[4 * j + 1]), pack_bf16(acc1[4 * j + 2], acc1[4 * j + 3]),
                pack_bf16(acc1[4 * j + 4], acc1[4 * j + 5]), pack_bf16(acc1[4 * j + 6], acc1[4 * j + 7]));
  }
  fence_async_smem();
  wg_bar(1 + cw);
  TSTAMP(isq ? 56 : 40 + 8 * cw);
  const int nsub = isq ? 2 : 1;
#pragma unroll 1
  for (int sub = 0; sub < nsub; sub++) {
    const int it = 4 * sub;
    (void)it;
    const uint32_t tile = sbase + OFF_PHI + (isq ? sub : 1) * 16384;
    const uint32_t wp = sbase + OFF_WPHI + (isq ? 2 * sub : 2 * cw) * 2048;
    float pq[4][16];
    uint32_t pos[4][8], neg[4][8];
    QT(0);
    wgmma_fence();
#pragma unroll
    for (int i = 0; i < 4; i++) {
      const uint32_t a = tile + (i & 1) * 8192 + (i >> 1) * 64, b = wp + (i >> 1) * 2048;
      wgmma_m64n32k16_ss_init<0, 1>(pq[i], make_desc(a, 16, 1024, 1), make_desc(b, 512, 512, 2));
      wgmma_m64n32k16_ss<0, 1>(pq[i], make_desc(a + 32, 16, 1024, 1), make_desc(b + 1024, 512, 512, 2));
    }
    wgmma_commit();
    wgmma_wait<0>();
#pragma unroll
    for (int i = 0; i < 4; i++) fence_regs(pq[i]);
    QT(1);
    dual_softmax_n<4>(pq, pos, neg);
    QT(2);
    if (!isq) {
      float kvacc[2][20];
      if (cw == 1) mbar_wait(sbase + OFF_BAR + B_EBF, 0);
#pragma unroll
      for (int hh = 0; hh < 2; hh++) {
#pragma unroll
        for (int half = 0; half < 2; half++) {
          const uint32_t rb = sbase + OFF_PHI + hh * 16384 + (half * 64 + row0) * 128;
#pragma unroll
          for (int jp = 0; jp < 2; jp++) {
            const int c0 = jp * 2 + (mi >> 1), i = 2 * hh + half;
            stmatrix_x4(rb + ((c0 ^ rin) << 4), pos[i][4 * jp], pos[i][4 * jp + 1], pos[i][4 * jp + 2], pos[i][4 * jp + 3]);
            stmatrix_x4(rb + (((c0 + 4) ^ rin) << 4), neg[i][4 * jp], neg[i][4 * jp + 1], neg[i][4 * jp + 2], neg[i][4 * jp + 3]);
          }
        }
      }
      fence_async_smem();
      wg_bar(1 + cw);
      wgmma_fence();
#pragma unroll
      for (int hh = 0; hh < 2; hh++)
#pragma unroll
        for (int ks = 0; ks < 8; ks++) {
          const uint32_t vb = sbase + OFF_V + hh * 8192 + ks * 1024;
          const uint64_t da = make_desc(sbase + OFF_PHI + hh * 16384 + ks * 2048, 1024, 1024, 1);
          const uint64_t db = make_desc(vb, sbase + OFF_ONES - vb, 512, 2);
          if (ks == 0) wgmma_m64n40k16_ss_init<1, 1>(kvacc[hh], da, db);
          else wgmma_m64n40k16_ss<1, 1>(kvacc[hh], da, db);
        }
      wgmma_commit();
      TSTAMP(42 + 8 * cw);
      wgmma_wait<0>();
      fence_regs(kvacc[0]);
      fence_regs(kvacc[1]);
      TSTAMP(43 + 8 * cw);
      wg_bar(1 + cw);
      if (t == 0) mbar_arrive(sbase + OFF_BAR + B_EBA);
#pragma unroll
      for (int hh = 0; hh < 2; hh++) {
#pragma unroll
        for (int rr = 0; rr < 2; rr++) {
          const int off = ((16 * w + r8 + 8 * rr) * KVW + 2 * q) * 4;
#pragma unroll
          for (int j = 0; j < 5; j++) {
            const int o = off + 32 * j;
            const uint32_t dst = (hh == 0) ? sbase + OFF_PHI + o
                                           : (o < 6144 ? sbase + OFF_PHI + 10240 + o : sbase + OFF_V + 16384 - 6144 + o);
            asm volatile("st.shared.v2.f32 [%0], {%1, %2};" ::"r"(dst), "f"(kvacc[hh][4 * j + 2 * rr]), "f"(kvacc[hh][4 * j + 2 * rr + 1]) : "memory");
          }
        }
      }
      fence_async_smem();
      wg_bar(1 + cw);
      if (t == 0) mbar_arrive(sbase + OFF_BAR + B_JOB + 16 + 8 * cw);
      TSTAMP(44 + 8 * cw);
    } else {
      float num[4][20];
      mbar_wait(sbase + OFF_BAR + B_KVX + 8 * sub, 0);
      TSTAMP(57 + sub);
      QT(3);
#pragma unroll
      for (int i = 0; i < 4; i++) q_issue_num(num[i], pos[i], neg[i], sbase + OFF_V + (2 * sub + (i >> 1)) * 5120);
      QT(4);
      wgmma_wait<2>();
      fence_regs(num[0]); fence_regs(num[1]);
      QT(5);
      q_store_o(num[0], tile + row0 * 128, 0);
      q_store_o(num[1], tile + 8192 + row0 * 128, 0);
      wgmma_wait<0>();
      fence_regs(num[2]); fence_regs(num[3]);
      QT(6);
      q_store_o(num[2], tile + row0 * 128, 4);
      q_store_o(num[3], tile + 8192 + row0 * 128, 4);
      QT(7);
      fence_async_smem();
      wg_bar(1);
      if (t == 0) mbar_arrive(sbase + OFF_BAR + B_JOB + 32 + 8 * sub);
    }
  }
}

__device__ __forceinline__ void helper_kv(uint32_t sbase, int g, unsigned epoch) {
  const int h = threadIdx.x - 64;
  mbar_wait(sbase + OFF_BAR + B_EBA, 0);
  mbar_wait(sbase + OFF_BAR + B_EBA, 1);
#pragma unroll 1
  for (int pr = 0; pr < 2; pr++) {
    if ((h & 31) == 0) wait_ge(sbase + OFF_BAR, &g_flags.kvcnt[(g + 8 * pr) * 8], 16u * epoch);
    __syncwarp();
    const float4* src = reinterpret_cast<const float4*>(g_kv + (size_t)(2 * g + 16 * pr) * 64 * KVW);
#pragma unroll 1
    for (int ib = 0; ib < 3; ib++) {
      float4 u[7];
#pragma unroll
      for (int i = 0; i < 7; i++) u[i] = __ldcg(src + min((ib * 7 + i) * 64 + h, 1279));
#pragma unroll
      for (int i = 0; i < 7; i++) {
        const int idx = min((ib * 7 + i) * 64 + h, 1279);
        const int f2 = idx / 10, j = idx - f2 * 10;
        const uint32_t dst = sbase + OFF_V + pr * 10240 + (f2 >> 3) * 640 + (j >> 1) * 128 + (f2 & 7) * 16 + (j & 1) * 8;
        asm volatile("st.shared.v2.b32 [%0], {%1, %2};" ::"r"(dst), "r"(pack_bf16(u[i].x, u[i].y)), "r"(pack_bf16(u[i].z, u[i].w)) : "memory");
      }
    }
    fence_async_smem();
    __syncwarp();
    if ((h & 31) == 0) mbar_arrive(sbase + OFF_BAR + B_KVX + 8 * pr);
  }
}

__device__ __forceinline__ void store_agent(const Params& prm, uint32_t sbase, int g, int rb, unsigned epoch) {
  const uint32_t bars = sbase + OFF_BAR;
#pragma unroll 1
  for (int j = 0; j < 6; j++) {
    mbar_wait(bars + B_JOB + 8 * j, 0);
    unsigned* flag;
    if (j < 2) {
      const int G = g + 8 * j;
      tma_store_3d(&prm.tmHT, sbase + OFF_PHI, 0, 64 * G, 2 * rb);
      tma_store_3d(&prm.tmHT, sbase + OFF_PHI + 16384, 0, 1024 + 64 * G, 2 * rb);
      flag = &g_flags.hcnt[rb * 8];
    } else if (j < 4) {
      const int hp = g + 8 * (j - 2);
      wait_ge(bars, &g_flags.zero_cnt, 128u * epoch);
      bulk_reduce_f32(g_kv + (size_t)(2 * hp) * 64 * KVW, sbase + OFF_PHI, 64 * KVW * 4);
      bulk_reduce_f32(g_kv + (size_t)(2 * hp + 1) * 64 * KVW, sbase + OFF_PHI + 10240, 6144);
      bulk_reduce_f32(g_kv + (size_t)(2 * hp + 1) * 64 * KVW + 1536, sbase + OFF_V + 16384, 4096);
      flag = &g_flags.kvcnt[hp * 8];
    } else {
      tma_store_2d(&prm.tmO, sbase + OFF_PHI + (j - 4) * 16384, 64 * (g + 8 * (j - 4)), 128 * rb);
      flag = &g_flags.ocnt[(2 * rb + (j - 4)) * 8];
    }
    bulk_commit();
    if (j != 4) {
      bulk_wait_read();
      mbar_arrive(bars + B_EBF);
    }
    bulk_wait_all();
    red_relaxed_add(flag, 1);
  }
}

constexpr int OST = 544;
__device__ __forceinline__ float bf16_round(float x) { return __bfloat162float(__float2bfloat16(x)); }
__device__ __forceinline__ void stage_half(const float (&a)[64], uint32_t wbuf) {
  const int lane = threadIdx.x & 31, q = lane & 3, r8 = lane >> 2;
#pragma unroll
  for (int j = 0; j < 16; j++) {
    asm volatile("st.shared.v2.f32 [%0], {%1, %2};" ::"r"(wbuf + r8 * OST + j * 32 + q * 8), "f"(a[4 * j]), "f"(a[4 * j + 1]) : "memory");
    asm volatile("st.shared.v2.f32 [%0], {%1, %2};" ::"r"(wbuf + (r8 + 8) * OST + j * 32 + q * 8), "f"(a[4 * j + 2]), "f"(a[4 * j + 3]) : "memory");
  }
  __syncwarp();
}
__device__ __forceinline__ float4 lds128(uint32_t addr) {
  float4 v;
  asm volatile("ld.shared.v4.f32 {%0, %1, %2, %3}, [%4];" : "=f"(v.x), "=f"(v.y), "=f"(v.z), "=f"(v.w) : "r"(addr) : "memory");
  return v;
}
template <bool IS_Y>
__device__ __forceinline__ void store_tile(float (&acc0)[64], const float (&acc1)[64], uint32_t wbuf, const Params& prm, int rb, int g) {
  const int lane = threadIdx.x & 31, w = (threadIdx.x & 127) >> 5;
  uint2 dk = make_uint2(0, 0);
  if (IS_Y) dk = __ldg(reinterpret_cast<const uint2*>(prm.dskip + 128 * g) + lane);
#pragma unroll 1
  for (int half = 0; half < 2; half++) {
    const int m0 = 64 * half + 16 * w;
    const int t0 = rb * 128 + (IS_Y ? 32 * ((m0 >> 3) & 3) + 8 * (m0 >> 5) : m0);
    uint2 xs[16];
    if (IS_Y) {
#pragma unroll
      for (int r = 0; r < 16; r++)
        xs[r] = __ldg(reinterpret_cast<const uint2*>(prm.xB + (size_t)(t0 + (r & 7) + (r >> 3) * 32) * DM + 128 * g) + lane);
    }
    stage_half(acc0, wbuf);
    float* dst = prm.out + (size_t)t0 * 2048 + (IS_Y ? 1024 : 0) + 128 * g + 4 * lane;
#pragma unroll
    for (int r = 0; r < 16; r++) {
      float4 v = lds128(wbuf + r * OST + lane * 16);
      if (IS_Y) {
        const float2 s0 = __bfloat1622float2(__hmul2(*reinterpret_cast<const __nv_bfloat162*>(&xs[r].x), *reinterpret_cast<const __nv_bfloat162*>(&dk.x)));
        const float2 s1 = __bfloat1622float2(__hmul2(*reinterpret_cast<const __nv_bfloat162*>(&xs[r].y), *reinterpret_cast<const __nv_bfloat162*>(&dk.y)));
        v.x += s0.x; v.y += s0.y; v.z += s1.x; v.w += s1.y;
      } else {
        v.x = bf16_round(v.x); v.y = bf16_round(v.y); v.z = bf16_round(v.z); v.w = bf16_round(v.w);
      }
      __stcs(reinterpret_cast<float4*>(dst + (size_t)((r & 7) + (r >> 3) * (IS_Y ? 32 : 8)) * 2048), v);
    }
    __syncwarp();
#pragma unroll
    for (int i = 0; i < 64; i++) acc0[i] = acc1[i];
  }
}

__global__ void __launch_bounds__(384, 1) fused_kernel(const __grid_constant__ Params prm) {
  extern __shared__ uint8_t smem_raw[];
  const uint32_t sbase = (smem_u32(smem_raw) + 1023) & ~1023u;
  const uint32_t bars = sbase + OFF_BAR;
  const int tid = threadIdx.x, wg = __shfl_sync(0xffffffffu, tid >> 7, 0);
  const int cl = blockIdx.x >> 1, rank = blockIdx.x & 1;
  const int g = cl >> 3, rb = 2 * (cl & 7) + rank;

  if (tid == 0) {
    for (int s = 0; s < STAGES; s++) { mbar_init(bars + 8 * s, 1);
      mbar_init(bars + B_EMPTY + 8 * s, 8);
    }
    mbar_init(bars + B_ORD, 1); mbar_init(bars + B_ORD + 8, 1); mbar_init(bars + B_EBF, 1); mbar_init(bars + B_WPHI, 1); mbar_init(bars + B_EPOCH, 1); mbar_init(bars + B_KVX, 2); mbar_init(bars + B_KVX + 8, 2);
    for (int j = 0; j < 6; j++) mbar_init(bars + B_JOB + 8 * j, 1);
    mbar_init(bars + B_PARAM, 2); mbar_init(bars + B_EBA, 1);
    asm volatile("st.shared.u32 [%0], %1;" ::"r"(bars + B_DEAD), "r"(0u) : "memory");
    asm volatile("fence.mbarrier_init.release.cluster;" ::: "memory");
  } else if (tid == 32) {
    prefetch_tm(&prm.tmXB); prefetch_tm(rank ? &prm.tmBim : &prm.tmBre); prefetch_tm(&prm.tmWphi);
    prefetch_tm(&prm.tmXA); prefetch_tm(&prm.tmWqkv); prefetch_tm(&prm.tmHT);
    prefetch_tm(&prm.tmCre); prefetch_tm(&prm.tmCim); prefetch_tm(&prm.tmO); prefetch_tm(&prm.tmWo);
  } else if (tid >= 64 && tid < 128) {
    asm volatile("st.shared.v4.b32 [%0], {%1, %2, %2, %2};" ::"r"(sbase + OFF_ONES + (tid - 64) * 16), "r"(0x00003F80u), "r"(0u) : "memory");
    fence_async_smem();
  }
  __syncthreads();
  asm volatile("barrier.cluster.arrive.relaxed.aligned;\nbarrier.cluster.wait.acquire.aligned;" ::: "memory");

  if (wg == 0) {
    reg_dealloc<56>();
    const int warp = __shfl_sync(0xffffffffu, tid >> 5, 0), lane = tid & 31;
    if (warp == 0) {
      const bool leader = elect_one();
      TSTAMP(0);
      if (leader) {
        mbar_expect_tx(bars + B_WPHI, 8192);
        tma_2d(sbase + OFF_WPHI, &prm.tmWphi, 0, 64 * g, bars + B_WPHI);
        tma_2d(sbase + OFF_WPHI + 4096, &prm.tmWphi, 0, 64 * g + 512, bars + B_WPHI);
      }
      int stage = 0;
      uint32_t phase = 1;
      unsigned epoch = 0;
      auto run = [&](auto kind, const CUtensorMap* tw, int w0, const CUtensorMap* tx, int kb0, int kb1) {
        constexpr int KIND = decltype(kind)::value;
#pragma unroll 1
        for (int kb = kb0; kb < kb1; kb++) {
          mbar_wait(bars + B_EMPTY + 8 * stage, phase);
          if (leader) {
            const uint32_t full = bars + 8 * stage;
            const uint32_t sw = sbase + stage * STAGE_BYTES;
            mbar_expect_tx(full, STAGE_BYTES);
            if (KIND == 0) {
              tma_2d_mc(sw + rank * 8192, tw, kb * 64, w0, full);
              tma_5d(sw + 16384, tx, kb * 64, 0, 0, 0, rb, full);
            } else if (KIND == 1) {
              tma_2d_mc(sw + rank * 8192, tw, w0, kb * 64, full);
              tma_2d(sw + 16384, tx, kb * 64, rb * 128, full);
            } else {
              tma_2d_mc(sw + rank * 8192, tw, (kb & 15) * 64, w0, full);
              tma_3d(sw + 16384, tx, 0, kb * 64, 2 * rb, full);
            }
          }
          if (++stage == STAGES) { stage = 0; phase ^= 1; }
        }
      };
      using K0 = std::integral_constant<int, 0>;
      using K1 = std::integral_constant<int, 1>;
      using K2 = std::integral_constant<int, 2>;
#pragma unroll 1
      for (int i = 0; i < 2; i++) run(K0{}, rank ? &prm.tmBim : &prm.tmBre, 64 * (g + 8 * i), &prm.tmXB, 0, 16);
#pragma unroll 1
      for (int i = 0; i < 3; i++)
        run(K1{}, &prm.tmWqkv, i < 2 ? 1024 + rank * 1024 + 64 * (g + 8 * i) : 64 * (g + 8 * rank), &prm.tmXA, 0, 16);
      mbar_wait(bars + B_EPOCH, 0);
      asm volatile("ld.shared.u32 %0, [%1];" : "=r"(epoch) : "r"(bars + B_EPOCHV) : "memory");
      wait_ge(bars, &g_flags.hcnt[rb * 8], 16u * epoch);
#pragma unroll 1
      for (int i = 0; i < 2; i++) run(K2{}, i ? &prm.tmCim : &prm.tmCre, 128 * g + 64 * rank, &prm.tmHT, 16 * i, 16 * i + 16);
#pragma unroll 1
      for (int i = 0; i < 2; i++) {
        wait_ge(bars, &g_flags.ocnt[(2 * rb + i) * 8], 8u * epoch);
        run(K1{}, &prm.tmWo, 128 * g + 64 * rank, &prm.tmO, 8 * i, 8 * i + 8);
      }
      TSTAMP(1);
    } else if (warp == 1) {
      unsigned epoch = 0;
      if (lane == 0) {
        epoch = (atomicAdd(&g_flags.ticket, 1u) >> 7) + 1u;
        asm volatile("st.shared.u32 [%0], %1;" ::"r"(bars + B_EPOCHV), "r"(epoch) : "memory");
        mbar_arrive(bars + B_EPOCH);
      }
      uint4* z = reinterpret_cast<uint4*>(g_kv) + blockIdx.x * 160;
#pragma unroll
      for (int i = 0; i < 5; i++) __stcg(z + i * 32 + lane, make_uint4(0, 0, 0, 0));
      __syncwarp();
      if (lane == 0) {
        red_release_add(&g_flags.zero_cnt, 1);
        store_agent(prm, sbase, g, rb, epoch);
      }
    } else {
#pragma unroll 1
      for (int c = 0; c < 2; c++) {
        const int ch = tid - 64, p = 64 * (g + 8 * c) + ch;
        const ChanParams cp = chan_params(__bfloat162float(prm.lam_re[p]), __bfloat162float(prm.lam_im[p]), __bfloat162float(prm.log_dt[p]));
        asm volatile("st.shared.v4.f32 [%0], {%1, %2, %3, %4};" ::"r"(sbase + OFF_V + (c * 64 + ch) * 16), "f"(cp.lam.r), "f"(cp.lam.i),
                     "f"(cp.c2.r), "f"(cp.c2.i) : "memory");
      }
      __syncwarp();
      if (lane == 0) mbar_arrive(bars + B_PARAM);
      unsigned epoch;
      mbar_wait(bars + B_EPOCH, 0);
      asm volatile("ld.shared.u32 %0, [%1];" : "=r"(epoch) : "r"(bars + B_EPOCHV) : "memory");
      helper_kv(sbase, g, epoch);
    }
    __syncwarp();
    asm volatile("barrier.cluster.arrive.relaxed.aligned;\nbarrier.cluster.wait.aligned;" ::: "memory");
  } else {
    reg_alloc<224>();
    const int cw = wg - 1;
    const int t = tid & 127, lane = t & 31, w = t >> 5, r8 = lane >> 2;
    float acc0[64], acc1[64];
    unsigned epoch;
    {
      const int G = g + 8 * cw;
      ChanParams cp[2];
      TSTAMP(2 + 12 * cw);
      mainloop<0>(acc0, acc1, 16 * cw, 16, sbase, cw, cw ^ 1);
      TSTAMP(3 + 12 * cw);
      mbar_wait(bars + B_PARAM, 0);
#pragma unroll
      for (int c = 0; c < 2; c++) {
        const float4 v = lds128(sbase + OFF_V + (cw * 64 + 16 * w + r8 + 8 * c) * 16);
        cp[c].lam = {v.x, v.y};
        cp[c].c2 = {v.z, v.w};
      }
      mbar_wait(bars + B_EPOCH, 0);
      asm volatile("ld.shared.u32 %0, [%1];" : "=r"(epoch) : "r"(bars + B_EPOCHV) : "memory");
      epi_bu(acc0, acc1, cp, sbase, G, rb, cw, epoch);
      TSTAMP(4 + 12 * cw);
    }
#pragma unroll 1
    for (int step = 0; step < 3; step++) {
      const int it0 = cw ? 48 : (step == 0 ? 32 : (step == 1 ? 64 : 112));
      mainloop<1>(acc0, acc1, it0, 16, sbase, cw, cw ? 1 : (step & 1));
      TSTAMP(step == 0 ? 5 + 12 * cw : (step == 1 ? 7 : 9));
      if (step == 2) {
        store_tile<false>(acc0, acc1, sbase + w * 16 * OST, prm, rb, g);
        TSTAMP(10);
        break;
      }
      mbar_wait(bars + B_WPHI, 0);
      if (cw == 1) {
        mbar_wait(bars + B_EBA, 0);
      } else {
        if (step == 1) mbar_wait(bars + B_EBA, 1);
        mbar_wait(bars + B_EBF, 1);
      }
      epi_attn(acc0, acc1, sbase, cw, step == 1);
      TSTAMP(step == 0 ? 6 + 12 * cw : 8);
      if (cw == 1) break;
    }
    if (cw == 1) {
      mainloop<2>(acc0, acc1, 80, 32, sbase, 1, 0);
      TSTAMP(19);
      mbar_wait(bars + B_EBF, 0);
      store_tile<true>(acc0, acc1, sbase + OFF_EB + w * 16 * OST, prm, rb, g);
      TSTAMP(20);
    }
    asm volatile("barrier.cluster.arrive.relaxed.aligned;\nbarrier.cluster.wait.aligned;" ::: "memory");
  }
}

typedef CUresult (*PFN_encodeTiled)(CUtensorMap*, CUtensorMapDataType, cuuint32_t, void*, const cuuint64_t*, const cuuint64_t*,
                                    const cuuint32_t*, const cuuint32_t*, CUtensorMapInterleave, CUtensorMapSwizzle,
                                    CUtensorMapL2promotion, CUtensorMapFloatOOBfill);

bool make_tm(PFN_encodeTiled enc, CUtensorMap* tm, const void* base, int rank, const uint64_t* dims, const uint64_t* strides,
             const uint32_t* box, CUtensorMapSwizzle sw) {
  cuuint64_t gd[5], gs[5];
  cuuint32_t bx[5], es[5];
  for (int i = 0; i < rank; i++) { gd[i] = dims[i]; bx[i] = box[i]; es[i] = 1; }
  for (int i = 0; i + 1 < rank; i++) gs[i] = strides[i];
  return enc(tm, CU_TENSOR_MAP_DATA_TYPE_BFLOAT16, rank, const_cast<void*>(base), gd, gs, bx, es, CU_TENSOR_MAP_INTERLEAVE_NONE, sw,
             CU_TENSOR_MAP_L2_PROMOTION_L2_256B, CU_TENSOR_MAP_FLOAT_OOB_FILL_NONE) == CUDA_SUCCESS;
}
bool make_tm2(PFN_encodeTiled enc, CUtensorMap* tm, const void* base, uint64_t inner, uint64_t outer, uint32_t b0, uint32_t b1,
              CUtensorMapSwizzle sw = CU_TENSOR_MAP_SWIZZLE_128B) {
  const uint64_t dims[2] = {inner, outer}, str[1] = {inner * 2};
  const uint32_t box[2] = {b0, b1};
  return make_tm(enc, tm, base, 2, dims, str, box, sw);
}

}

extern "C" void kernel_launch(void* const* d_in, const int* in_sizes, int n_in, void* d_out, int out_size) {
  (void)in_sizes; (void)n_in; (void)out_size;
  static PFN_encodeTiled enc = nullptr;
  static void *pHT = nullptr, *pO = nullptr;
  if (!enc) {
    void* fn = nullptr;
    cudaDriverEntryPointQueryResult qr;
    if (cudaGetDriverEntryPoint("cuTensorMapEncodeTiled", &fn, cudaEnableDefault, &qr) != cudaSuccess || !fn) return;
    enc = (PFN_encodeTiled)fn;
    cudaFuncSetAttribute(fused_kernel, cudaFuncAttributeMaxDynamicSharedMemorySize, SMEM_BYTES);
    cudaGetSymbolAddress(&pHT, g_HT);
    cudaGetSymbolAddress(&pO, g_O);
  }
  Params prm;
  bool ok = true;
  {
    const uint64_t dims[5] = {1024, 2, 4, 16, 16}, str[4] = {2048, 65536, 4096, 262144};
    const uint32_t box[5] = {64, 2, 4, 16, 1};
    ok &= make_tm(enc, &prm.tmXB, d_in[4], 5, dims, str, box, CU_TENSOR_MAP_SWIZZLE_128B);
  }
  ok &= make_tm2(enc, &prm.tmBre, d_in[7], 1024, 1024, 64, 64);
  ok &= make_tm2(enc, &prm.tmBim, d_in[8], 1024, 1024, 64, 64);
  ok &= make_tm2(enc, &prm.tmXA, d_in[0], 1024, 2048, 64, 128);
  ok &= make_tm2(enc, &prm.tmWqkv, d_in[1], 3072, 1024, 64, 64);
  ok &= make_tm2(enc, &prm.tmWphi, d_in[2], 32, 1024, 32, 64, CU_TENSOR_MAP_SWIZZLE_64B);
  {
    const uint64_t dims[3] = {64, 2048, 32}, str[2] = {4096, 128};
    const uint32_t box[3] = {64, 64, 2};
    ok &= make_tm(enc, &prm.tmHT, pHT, 3, dims, str, box, CU_TENSOR_MAP_SWIZZLE_128B);
  }
  ok &= make_tm2(enc, &prm.tmCre, d_in[9], 1024, 1024, 64, 64);
  ok &= make_tm2(enc, &prm.tmCim, d_in[10], 1024, 1024, 64, 64);
  ok &= make_tm2(enc, &prm.tmO, pO, 1024, 2048, 64, 128);
  ok &= make_tm2(enc, &prm.tmWo, d_in[3], 1024, 1024, 64, 64);
  if (!ok) return;
  prm.xB = (const __nv_bfloat16*)d_in[4];
  prm.lam_re = (const __nv_bfloat16*)d_in[5];
  prm.lam_im = (const __nv_bfloat16*)d_in[6];
  prm.log_dt = (const __nv_bfloat16*)d_in[11];
  prm.dskip = (const __nv_bfloat16*)d_in[12];
  prm.out = (float*)d_out;

  cudaLaunchConfig_t cfg = {};
  cfg.gridDim = dim3(128);
  cfg.blockDim = dim3(384);
  cfg.dynamicSmemBytes = SMEM_BYTES;
  cfg.stream = cudaStreamPerThread;
  cudaLaunchAttribute attr[1];
  attr[0].id = cudaLaunchAttributeClusterDimension;
  attr[0].val.clusterDim.x = 2; attr[0].val.clusterDim.y = 1; attr[0].val.clusterDim.z = 1;
  cfg.attrs = attr;
  cfg.numAttrs = 1;
  cudaLaunchKernelEx(&cfg, fused_kernel, prm);
}
```

```cpp
#include <cuda_runtime.h>
#include <cuda_bf16.h>
#include <cuda.h>
#include <stdint.h>
#include <type_traits>

namespace {

constexpr int SEQ = 2048;
constexpr int DM = 1024;
#define NSTAGES 5
constexpr int STAGES = NSTAGES;
constexpr int STAGE_BYTES = 32768;
constexpr int OFF_EB = 5 * STAGE_BYTES;
constexpr int OFF_PHI = OFF_EB;
constexpr int OFF_V = OFF_EB + 32768;
constexpr int OFF_WPHI = OFF_EB + 53248;
constexpr int OFF_ONES = OFF_EB + 61440;
constexpr int OFF_BAR = OFF_EB + 62464;
constexpr int SMEM_BYTES = OFF_BAR + 512 + 1024;
constexpr int B_EMPTY = 64, B_ORD = 128  , B_WPHI = 144, B_EPOCH = 152, B_PARAM = 160, B_KVX = 168  , B_EBA = 184  ,
              B_EPOCHV = 200, B_DEAD = 204, B_JOB = 208  , B_EBF = 256  ;

constexpr int KVW = 40;

struct Params {
  CUtensorMap tmXB;
  CUtensorMap tmBre, tmBim;
  CUtensorMap tmXA;
  CUtensorMap tmWqkv;
  CUtensorMap tmWphi;
  CUtensorMap tmHT;
  CUtensorMap tmHTs;
  CUtensorMap tmCre, tmCim;
  CUtensorMap tmO;
  CUtensorMap tmWo;
  const __nv_bfloat16* xB;
  const __nv_bfloat16* lam_re;
  const __nv_bfloat16* lam_im;
  const __nv_bfloat16* log_dt;
  const __nv_bfloat16* dskip;
  float* out;
};

__device__ __nv_bfloat16 g_HT[2048 * 2048];
__device__ __nv_bfloat16 g_O[SEQ * DM];
__device__ float g_kv[32 * 64 * KVW];
__device__ uint4 g_E[16 * 16 * 64];
struct Flags {
  unsigned ticket;   unsigned pad0[31];
  unsigned zero_cnt; unsigned pad1[31];
  unsigned hcnt[16 * 8];
  unsigned kvcnt[16 * 8];
  unsigned ocnt[2 * 16 * 8];
};
__device__ Flags g_flags;
#define TSTAMP(i)
#define QT(i)

__device__ __forceinline__ uint32_t smem_u32(const void* p) { return (uint32_t)__cvta_generic_to_shared(p); }
__device__ __forceinline__ void mbar_init(uint32_t bar, uint32_t count) {
  asm volatile("mbarrier.init.shared::cta.b64 [%0], %1;" ::"r"(bar), "r"(count));
}
__device__ __forceinline__ void mbar_expect_tx(uint32_t bar, uint32_t bytes) {
  asm volatile("mbarrier.arrive.expect_tx.shared::cta.b64 _, [%0], %1;" ::"r"(bar), "r"(bytes) : "memory");
}
__device__ __forceinline__ void mbar_arrive(uint32_t bar) {
  asm volatile("mbarrier.arrive.shared::cta.b64 _, [%0];" ::"r"(bar) : "memory");
}
__device__ __forceinline__ void mbar_arrive_cluster(uint32_t bar, uint32_t cta) {
  asm volatile("{\n.reg .b32 ra;\nmapa.shared::cluster.u32 ra, %0, %1;\nmbarrier.arrive.shared::cluster.b64 _, [ra];\n}" ::"r"(bar), "r"(cta) : "memory");
}
__device__ __forceinline__ uint32_t dead_addr(uint32_t bar) { return (bar & ~0x1FFu) + B_DEAD; }
__device__ __forceinline__ void mbar_wait(uint32_t bar, uint32_t parity) {
  asm volatile(
      "{\n.reg .pred p;\n.reg .u32 c, d;\n"
      "mov.u32 c, 0;\n"
      "WAIT_LOOP:\n"
      "mbarrier.try_wait.parity.shared::cta.b64 p, [%0], %1;\n"
      "@p bra WAIT_DONE;\n"
      "add.u32 c, c, 1;\n"
      "setp.gt.u32 p, c, 0x200000;\n"
      "@p st.volatile.shared.u32 [%2], c;\n"
      "ld.volatile.shared.u32 d, [%2];\n"
      "setp.eq.u32 p, d, 0;\n"
      "@p bra WAIT_LOOP;\n"
      "WAIT_DONE:\n}\n" ::"r"(bar), "r"(parity), "r"(dead_addr(bar)) : "memory");
}
__device__ __forceinline__ void mbar_wait_long(uint32_t bar, uint32_t parity) {
  asm volatile(
      "{\n.reg .pred p;\n.reg .u32 c, d;\n"
      "mov.u32 c, 0;\n"
      "WAITL_LOOP:\n"
      "mbarrier.try_wait.parity.shared::cta.b64 p, [%0], %1;\n"
      "@p bra WAITL_DONE;\n"
      "nanosleep.u32 100;\n"
      "add.u32 c, c, 1;\n"
      "setp.gt.u32 p, c, 0x200000;\n"
      "@p st.volatile.shared.u32 [%2], c;\n"
      "ld.volatile.shared.u32 d, [%2];\n"
      "setp.eq.u32 p, d, 0;\n"
      "@p bra WAITL_LOOP;\n"
      "WAITL_DONE:\n}\n" ::"r"(bar), "r"(parity), "r"(dead_addr(bar)) : "memory");
}
__device__ __forceinline__ bool give_up(uint32_t bars, unsigned spins) {
  unsigned d;
  if (spins > (1u << 20)) asm volatile("st.volatile.shared.u32 [%0], %1;" ::"r"(bars + B_DEAD), "r"(spins) : "memory");
  asm volatile("ld.volatile.shared.u32 %0, [%1];" : "=r"(d) : "r"(bars + B_DEAD) : "memory");
  return d != 0;
}
__device__ __forceinline__ unsigned ld_relaxed(const unsigned* p) {
  unsigned v;
  asm volatile("ld.relaxed.gpu.global.u32 %0, [%1];" : "=r"(v) : "l"(p) : "memory");
  return v;
}
__device__ __forceinline__ void wait_ge(uint32_t bars, const unsigned* p, unsigned target) {
  unsigned spins = 0;
  while ((int)(ld_relaxed(p) - target) < 0) {
    __nanosleep(128);
    if (give_up(bars, ++spins)) break;
  }
  unsigned v;
  asm volatile("ld.acquire.gpu.global.u32 %0, [%1];" : "=r"(v) : "l"(p) : "memory");
}
__device__ __forceinline__ void red_release_add(unsigned* p, unsigned v) {
  asm volatile("red.release.gpu.global.add.u32 [%0], %1;" ::"l"(p), "r"(v) : "memory");
}
__device__ __forceinline__ void red_relaxed_add(unsigned* p, unsigned v) {
  asm volatile("red.relaxed.gpu.global.add.u32 [%0], %1;" ::"l"(p), "r"(v) : "memory");
}
__device__ __forceinline__ void st_tagged(uint4* p, float a, float b, unsigned tag) {
  const unsigned long long w0 = ((unsigned long long)tag << 32) | __float_as_uint(a);
  const unsigned long long w1 = ((unsigned long long)tag << 32) | __float_as_uint(b);
  asm volatile("st.relaxed.gpu.global.v2.b64 [%0], {%1, %2};" ::"l"(p), "l"(w0), "l"(w1) : "memory");
}
__device__ __forceinline__ void bulk_commit() { asm volatile("cp.async.bulk.commit_group;" ::: "memory"); }
__device__ __forceinline__ void bulk_wait_read() { asm volatile("cp.async.bulk.wait_group.read 0;" ::: "memory"); }
__device__ __forceinline__ void bulk_wait_all() { asm volatile("cp.async.bulk.wait_group 0;" ::: "memory"); }
__device__ __forceinline__ void bulk_reduce_f32(float* dst, uint32_t src, uint32_t bytes) {
  asm volatile("cp.reduce.async.bulk.global.shared::cta.bulk_group.add.f32 [%0], [%1], %2;" ::"l"(dst), "r"(src), "r"(bytes) : "memory");
}
__device__ __forceinline__ void tma_store_3d(const CUtensorMap* tm, uint32_t src, int c0, int c1, int c2) {
  asm volatile("cp.async.bulk.tensor.3d.global.shared::cta.bulk_group [%0, {%2, %3, %4}], [%1];"
               ::"l"(tm), "r"(src), "r"(c0), "r"(c1), "r"(c2) : "memory");
}
__device__ __forceinline__ void fence_gpu() { asm volatile("fence.acq_rel.gpu;" ::: "memory"); }
__device__ __forceinline__ void fence_async_global() { asm volatile("fence.proxy.async.global;" ::: "memory"); }
__device__ __forceinline__ void fence_async_smem() { asm volatile("fence.proxy.async.shared::cta;" ::: "memory"); }
__device__ __forceinline__ void tma_2d(uint32_t dst, const CUtensorMap* tm, int c0, int c1, uint32_t bar) {
  asm volatile("cp.async.bulk.tensor.2d.shared::cluster.global.mbarrier::complete_tx::bytes [%0], [%1, {%3, %4}], [%2];"
               ::"r"(dst), "l"(tm), "r"(bar), "r"(c0), "r"(c1) : "memory");
}
__device__ __forceinline__ void tma_3d(uint32_t dst, const CUtensorMap* tm, int c0, int c1, int c2, uint32_t bar) {
  asm volatile("cp.async.bulk.tensor.3d.shared::cluster.global.mbarrier::complete_tx::bytes [%0], [%1, {%3, %4, %5}], [%2];"
               ::"r"(dst), "l"(tm), "r"(bar), "r"(c0), "r"(c1), "r"(c2) : "memory");
}
__device__ __forceinline__ void tma_5d(uint32_t dst, const CUtensorMap* tm, int c0, int c1, int c2, int c3, int c4, uint32_t bar) {
  asm volatile("cp.async.bulk.tensor.5d.shared::cluster.global.mbarrier::complete_tx::bytes [%0], [%1, {%3, %4, %5, %6, %7}], [%2];"
               ::"r"(dst), "l"(tm), "r"(bar), "r"(c0), "r"(c1), "r"(c2), "r"(c3), "r"(c4) : "memory");
}
__device__ __forceinline__ void tma_2d_mc(uint32_t dst, const CUtensorMap* tm, int c0, int c1, uint32_t bar) {
  asm volatile("cp.async.bulk.tensor.2d.shared::cluster.global.mbarrier::complete_tx::bytes.multicast::cluster [%0], [%1, {%3, %4}], [%2], %5;"
               ::"r"(dst), "l"(tm), "r"(bar), "r"(c0), "r"(c1), "h"((uint16_t)3) : "memory");
}
__device__ __forceinline__ void tma_store_2d(const CUtensorMap* tm, uint32_t src, int c0, int c1) {
  asm volatile("cp.async.bulk.tensor.2d.global.shared::cta.bulk_group [%0, {%2, %3}], [%1];"
               ::"l"(tm), "r"(src), "r"(c0), "r"(c1) : "memory");
}
__device__ __forceinline__ bool elect_one() {
  uint32_t p;
  asm volatile("{\n.reg .pred e;\nelect.sync _|e, 0xffffffff;\nselp.u32 %0, 1, 0, e;\n}" : "=r"(p));
  return p != 0;
}
__device__ __forceinline__ void prefetch_tm(const CUtensorMap* tm) {
  asm volatile("prefetch.tensormap [%0];" ::"l"(tm) : "memory");
}
__device__ __forceinline__ void wgmma_fence() { asm volatile("wgmma.fence.sync.aligned;" ::: "memory"); }
__device__ __forceinline__ void wgmma_commit() { asm volatile("wgmma.commit_group.sync.aligned;" ::: "memory"); }
template <int N> __device__ __forceinline__ void wgmma_wait() { asm volatile("wgmma.wait_group.sync.aligned %0;" ::"n"(N) : "memory"); }
__device__ __forceinline__ void wg_bar(int id) {
  if (id == 1) asm volatile("bar.sync 1, 128;" ::: "memory");
  else asm volatile("bar.sync 2, 128;" ::: "memory");
}
template <int R> __device__ __forceinline__ void reg_alloc() { asm volatile("setmaxnreg.inc.sync.aligned.u32 %0;" ::"n"(R)); }
template <int R> __device__ __forceinline__ void reg_dealloc() { asm volatile("setmaxnreg.dec.sync.aligned.u32 %0;" ::"n"(R)); }

__device__ __forceinline__ uint64_t make_desc(uint32_t saddr, uint32_t lbo_bytes, uint32_t sbo_bytes, uint32_t layout) {
  uint64_t d = (uint64_t)((saddr & 0x3FFFF) >> 4);
  d |= (uint64_t)((lbo_bytes & 0x3FFFF) >> 4) << 16;
  d |= (uint64_t)((sbo_bytes & 0x3FFFF) >> 4) << 32;
  d |= (uint64_t)layout << 62;
  return d;
}
__device__ __forceinline__ uint64_t desc128(uint32_t lo) { return ((uint64_t)0x40000040u << 32) | lo; }
__device__ __forceinline__ uint32_t pack_bf16(float lo, float hi) {
  uint32_t r;
  asm("cvt.rn.bf16x2.f32 %0, %1, %2;" : "=r"(r) : "f"(hi), "f"(lo));
  return r;
}
__device__ __forceinline__ float ex2(float x) { float y; asm("ex2.approx.ftz.f32 %0, %1;" : "=f"(y) : "f"(x)); return y; }
__device__ __forceinline__ float rcp(float x) { float y; asm("rcp.approx.ftz.f32 %0, %1;" : "=f"(y) : "f"(x)); return y; }
__device__ __forceinline__ void stmatrix_x4(uint32_t addr, uint32_t r0, uint32_t r1, uint32_t r2, uint32_t r3) {
  asm volatile("stmatrix.sync.aligned.m8n8.x4.shared.b16 [%0], {%1, %2, %3, %4};" ::"r"(addr), "r"(r0), "r"(r1), "r"(r2), "r"(r3) : "memory");
}
template <int N> __device__ __forceinline__ void fence_regs(float (&d)[N]) {
#pragma unroll
  for (int i = 0; i < N; i++) asm volatile("" : "+f"(d[i])::"memory");
}

template <int TA, int TB>
__device__ __forceinline__ void wgmma_m64n128k16_ss(float (&d)[64], uint64_t descA, uint64_t descB) {
  asm volatile("{\n.reg .pred p;\nsetp.ne.b32 p, 1, 0;\n"
    "wgmma.mma_async.sync.aligned.m64n128k16.f32.bf16.bf16 "
    "{%0, %1, %2, %3, %4, %5, %6, %7, %8, %9, %10, %11, %12, %13, %14, %15, %16, %17, %18, %19, %20, %21, %22, %23, %24, %25, %26, %27, %28, %29, %30, %31, %32, %33, %34, %35, %36, %37, %38, %39, %40, %41, %42, %43, %44, %45, %46, %47, %48, %49, %50, %51, %52, %53, %54, %55, %56, %57, %58, %59, %60, %61, %62, %63}, "
    "%64, %65, p, 1, 1, %66, %67;\n}\n"
    : "+f"(d[0]), "+f"(d[1]), "+f"(d[2]), "+f"(d[3]), "+f"(d[4]), "+f"(d[5]), "+f"(d[6]), "+f"(d[7]), "+f"(d[8]), "+f"(d[9]), "+f"(d[10]), "+f"(d[11]), "+f"(d[12]), "+f"(d[13]), "+f"(d[14]), "+f"(d[15]), "+f"(d[16]), "+f"(d[17]), "+f"(d[18]), "+f"(d[19]), "+f"(d[20]), "+f"(d[21]), "+f"(d[22]), "+f"(d[23]), "+f"(d[24]), "+f"(d[25]), "+f"(d[26]), "+f"(d[27]), "+f"(d[28]), "+f"(d[29]), "+f"(d[30]), "+f"(d[31]), "+f"(d[32]), "+f"(d[33]), "+f"(d[34]), "+f"(d[35]), "+f"(d[36]), "+f"(d[37]), "+f"(d[38]), "+f"(d[39]), "+f"(d[40]), "+f"(d[41]), "+f"(d[42]), "+f"(d[43]), "+f"(d[44]), "+f"(d[45]), "+f"(d[46]), "+f"(d[47]), "+f"(d[48]), "+f"(d[49]), "+f"(d[50]), "+f"(d[51]), "+f"(d[52]), "+f"(d[53]), "+f"(d[54]), "+f"(d[55]), "+f"(d[56]), "+f"(d[57]), "+f"(d[58]), "+f"(d[59]), "+f"(d[60]), "+f"(d[61]), "+f"(d[62]), "+f"(d[63])
    : "l"(descA), "l"(descB), "n"(TA), "n"(TB));
}

template <int TA, int TB>
__device__ __forceinline__ void wgmma_m64n32k16_ss(float (&d)[16], uint64_t descA, uint64_t descB) {
  asm volatile("{\n.reg .pred p;\nsetp.ne.b32 p, 1, 0;\n"
    "wgmma.mma_async.sync.aligned.m64n32k16.f32.bf16.bf16 "
    "{%0, %1, %2, %3, %4, %5, %6, %7, %8, %9, %10, %11, %12, %13, %14, %15}, "
    "%16, %17, p, 1, 1, %18, %19;\n}\n"
    : "+f"(d[0]), "+f"(d[1]), "+f"(d[2]), "+f"(d[3]), "+f"(d[4]), "+f"(d[5]), "+f"(d[6]), "+f"(d[7]), "+f"(d[8]), "+f"(d[9]), "+f"(d[10]), "+f"(d[11]), "+f"(d[12]), "+f"(d[13]), "+f"(d[14]), "+f"(d[15])
    : "l"(descA), "l"(descB), "n"(TA), "n"(TB));
}

template <int TA, int TB>
__device__ __forceinline__ void wgmma_m64n32k16_ss_init(float (&d)[16], uint64_t descA, uint64_t descB) {
  asm volatile("{\n.reg .pred p;\nsetp.ne.b32 p, 0, 0;\n"
    "wgmma.mma_async.sync.aligned.m64n32k16.f32.bf16.bf16 "
    "{%0, %1, %2, %3, %4, %5, %6, %7, %8, %9, %10, %11, %12, %13, %14, %15}, "
    "%16, %17, p, 1, 1, %18, %19;\n}\n"
    : "=f"(d[0]), "=f"(d[1]), "=f"(d[2]), "=f"(d[3]), "=f"(d[4]), "=f"(d[5]), "=f"(d[6]), "=f"(d[7]), "=f"(d[8]), "=f"(d[9]), "=f"(d[10]), "=f"(d[11]), "=f"(d[12]), "=f"(d[13]), "=f"(d[14]), "=f"(d[15])
    : "l"(descA), "l"(descB), "n"(TA), "n"(TB));
}

template <int TA, int TB>
__device__ __forceinline__ void wgmma_m64n40k16_ss(float (&d)[20], uint64_t descA, uint64_t descB) {
  asm volatile("{\n.reg .pred p;\nsetp.ne.b32 p, 1, 0;\n"
    "wgmma.mma_async.sync.aligned.m64n40k16.f32.bf16.bf16 "
    "{%0, %1, %2, %3, %4, %5, %6, %7, %8, %9, %10, %11, %12, %13, %14, %15, %16, %17, %18, %19}, "
    "%20, %21, p, 1, 1, %22, %23;\n}\n"
    : "+f"(d[0]), "+f"(d[1]), "+f"(d[2]), "+f"(d[3]), "+f"(d[4]), "+f"(d[5]), "+f"(d[6]), "+f"(d[7]), "+f"(d[8]), "+f"(d[9]), "+f"(d[10]), "+f"(d[11]), "+f"(d[12]), "+f"(d[13]), "+f"(d[14]), "+f"(d[15]), "+f"(d[16]), "+f"(d[17]), "+f"(d[18]), "+f"(d[19])
    : "l"(descA), "l"(descB), "n"(TA), "n"(TB));
}

template <int TA, int TB>
__device__ __forceinline__ void wgmma_m64n40k16_ss_init(float (&d)[20], uint64_t descA, uint64_t descB) {
  asm volatile("{\n.reg .pred p;\nsetp.ne.b32 p, 0, 0;\n"
    "wgmma.mma_async.sync.aligned.m64n40k16.f32.bf16.bf16 "
    "{%0, %1, %2, %3, %4, %5, %6, %7, %8, %9, %10, %11, %12, %13, %14, %15, %16, %17, %18, %19}, "
    "%20, %21, p, 1, 1, %22, %23;\n}\n"
    : "=f"(d[0]), "=f"(d[1]), "=f"(d[2]), "=f"(d[3]), "=f"(d[4]), "=f"(d[5]), "=f"(d[6]), "=f"(d[7]), "=f"(d[8]), "=f"(d[9]), "=f"(d[10]), "=f"(d[11]), "=f"(d[12]), "=f"(d[13]), "=f"(d[14]), "=f"(d[15]), "=f"(d[16]), "=f"(d[17]), "=f"(d[18]), "=f"(d[19])
    : "l"(descA), "l"(descB), "n"(TA), "n"(TB));
}

template <int TB>
__device__ __forceinline__ void wgmma_m64n40k16_rs(float (&d)[20], uint32_t a0, uint32_t a1, uint32_t a2, uint32_t a3, uint64_t descB) {
  asm volatile("{\n.reg .pred p;\nsetp.ne.b32 p, 1, 0;\n"
    "wgmma.mma_async.sync.aligned.m64n40k16.f32.bf16.bf16 "
    "{%0, %1, %2, %3, %4, %5, %6, %7, %8, %9, %10, %11, %12, %13, %14, %15, %16, %17, %18, %19}, "
    "{%20, %21, %22, %23}, %24, p, 1, 1, %25;\n}\n"
    : "+f"(d[0]), "+f"(d[1]), "+f"(d[2]), "+f"(d[3]), "+f"(d[4]), "+f"(d[5]), "+f"(d[6]), "+f"(d[7]), "+f"(d[8]), "+f"(d[9]), "+f"(d[10]), "+f"(d[11]), "+f"(d[12]), "+f"(d[13]), "+f"(d[14]), "+f"(d[15]), "+f"(d[16]), "+f"(d[17]), "+f"(d[18]), "+f"(d[19])
    : "r"(a0), "r"(a1), "r"(a2), "r"(a3), "l"(descB), "n"(TB));
}

template <int TB>
__device__ __forceinline__ void wgmma_m64n40k16_rs_init(float (&d)[20], uint32_t a0, uint32_t a1, uint32_t a2, uint32_t a3, uint64_t descB) {
  asm volatile("{\n.reg .pred p;\nsetp.ne.b32 p, 0, 0;\n"
    "wgmma.mma_async.sync.aligned.m64n40k16.f32.bf16.bf16 "
    "{%0, %1, %2, %3, %4, %5, %6, %7, %8, %9, %10, %11, %12, %13, %14, %15, %16, %17, %18, %19}, "
    "{%20, %21, %22, %23}, %24, p, 1, 1, %25;\n}\n"
    : "=f"(d[0]), "=f"(d[1]), "=f"(d[2]), "=f"(d[3]), "=f"(d[4]), "=f"(d[5]), "=f"(d[6]), "=f"(d[7]), "=f"(d[8]), "=f"(d[9]), "=f"(d[10]), "=f"(d[11]), "=f"(d[12]), "=f"(d[13]), "=f"(d[14]), "=f"(d[15]), "=f"(d[16]), "=f"(d[17]), "=f"(d[18]), "=f"(d[19])
    : "r"(a0), "r"(a1), "r"(a2), "r"(a3), "l"(descB), "n"(TB));
}

template <int MODE>
__device__ __forceinline__ void mainloop(float (&acc0)[64], float (&acc1)[64], int it0, int nkb, uint32_t sbase, int cw,
                                         uint32_t ord_parity) {
  const uint32_t bars = sbase + OFF_BAR;
  const int lane = threadIdx.x & 31;
  int stage = it0 % STAGES;
  uint32_t phase = (it0 / STAGES) & 1;
#pragma unroll
  for (int i = 0; i < 64; i++) { acc0[i] = 0.f; acc1[i] = 0.f; }
  mbar_wait(bars + B_ORD + 8 * cw, ord_parity);
  int prev = 0;
  for (int kb = 0; kb < nkb; kb++) {
    mbar_wait(bars + 8 * stage, phase);
    if (kb == nkb - 1 && (threadIdx.x & 127) == 0) mbar_arrive(bars + B_ORD + 8 * (cw ^ 1));
    const uint32_t lo = ((sbase & 0x3FFFFu) + stage * STAGE_BYTES) >> 4;
    const uint32_t loK = lo | (1u << 16), loM = lo | (512u << 16);
    wgmma_fence();
#pragma unroll
    for (int k = 0; k < 4; k++) {
      if (MODE == 0) {
        const uint64_t dx = desc128(loK + 1024 + 2 * k);
        wgmma_m64n128k16_ss<0, 0>(acc0, desc128(loK + 2 * k), dx);
        wgmma_m64n128k16_ss<0, 0>(acc1, desc128(loK + 512 + 2 * k), dx);
      } else if (MODE == 1) {
        const uint64_t dw = desc128(loM + 128 * k);
        wgmma_m64n128k16_ss<0, 1>(acc0, desc128(loK + 1024 + 2 * k), dw);
        wgmma_m64n128k16_ss<0, 1>(acc1, desc128(loK + 1536 + 2 * k), dw);
      } else {
        const uint64_t dw = desc128(loK + 2 * k);
        wgmma_m64n128k16_ss<1, 0>(acc0, desc128(loM + 1024 + 128 * k), dw);
        wgmma_m64n128k16_ss<1, 0>(acc1, desc128(loM + 1536 + 128 * k), dw);
      }
    }
    wgmma_commit();
    wgmma_wait<1>();
    if (kb > 0 && lane < 2) mbar_arrive_cluster(bars + B_EMPTY + 8 * prev, lane);
    prev = stage;
    if (++stage == STAGES) { stage = 0; phase ^= 1; }
  }
  wgmma_wait<0>();
  if (lane < 2) mbar_arrive_cluster(bars + B_EMPTY + 8 * prev, lane);
  fence_regs(acc0);
  fence_regs(acc1);
}

template <int N>
__device__ __forceinline__ void dual_softmax_n(const float (&p)[N][16], uint32_t (&pos)[N][8], uint32_t (&neg)[N][8]) {
  constexpr float L2E = 1.4426950408889634f;
  float ca[N][2], cb[N][2];
  {
    float mx[N][2], mn[N][2];
#pragma unroll
    for (int i = 0; i < N; i++)
#pragma unroll
      for (int r = 0; r < 2; r++) {
        const int o = 2 * r;
        mx[i][r] = fmaxf(fmaxf(fmaxf(p[i][o], p[i][o + 1]), fmaxf(p[i][4 + o], p[i][5 + o])),
                         fmaxf(fmaxf(p[i][8 + o], p[i][9 + o]), fmaxf(p[i][12 + o], p[i][13 + o])));
        mn[i][r] = fminf(fminf(fminf(p[i][o], p[i][o + 1]), fminf(p[i][4 + o], p[i][5 + o])),
                         fminf(fminf(p[i][8 + o], p[i][9 + o]), fminf(p[i][12 + o], p[i][13 + o])));
      }
#pragma unroll
    for (int o = 1; o <= 2; o <<= 1) {
      float tx[N][2], tn[N][2];
#pragma unroll
      for (int i = 0; i < N; i++)
#pragma unroll
        for (int r = 0; r < 2; r++) { tx[i][r] = __shfl_xor_sync(0xffffffffu, mx[i][r], o); tn[i][r] = __shfl_xor_sync(0xffffffffu, mn[i][r], o); }
#pragma unroll
      for (int i = 0; i < N; i++)
#pragma unroll
        for (int r = 0; r < 2; r++) { mx[i][r] = fmaxf(mx[i][r], tx[i][r]); mn[i][r] = fminf(mn[i][r], tn[i][r]); }
    }
#pragma unroll
    for (int i = 0; i < N; i++)
#pragma unroll
      for (int r = 0; r < 2; r++) { ca[i][r] = -mx[i][r] * L2E; cb[i][r] = mn[i][r] * L2E; }
  }
  float ep[2][16], en[2][16];
  float rp[2], rn[2];
#pragma unroll
  for (int i = 0; i <= N; i++) {
    const int cur = i & 1, prv = cur ^ 1;
    if (i > 0) {
      float sp[2], sn[2];
#pragma unroll
      for (int r = 0; r < 2; r++) {
        const int o = 2 * r;
        sp[r] = ((ep[prv][o] + ep[prv][o + 1]) + (ep[prv][4 + o] + ep[prv][5 + o])) + ((ep[prv][8 + o] + ep[prv][9 + o]) + (ep[prv][12 + o] + ep[prv][13 + o]));
        sn[r] = ((en[prv][o] + en[prv][o + 1]) + (en[prv][4 + o] + en[prv][5 + o])) + ((en[prv][8 + o] + en[prv][9 + o]) + (en[prv][12 + o] + en[prv][13 + o]));
      }
      float t0[2], t1[2];
#pragma unroll
      for (int r = 0; r < 2; r++) { t0[r] = __shfl_xor_sync(0xffffffffu, sp[r], 1); t1[r] = __shfl_xor_sync(0xffffffffu, sn[r], 1); }
      if (i < N) {
#pragma unroll
        for (int e = 0; e < 4; e++) {
          ep[cur][e] = ex2(fmaf(p[i][e], L2E, ca[i][e >> 1])); en[cur][e] = ex2(fmaf(p[i][e], -L2E, cb[i][e >> 1]));
        }
      }
#pragma unroll
      for (int r = 0; r < 2; r++) { sp[r] += t0[r]; sn[r] += t1[r]; }
#pragma unroll
      for (int r = 0; r < 2; r++) { t0[r] = __shfl_xor_sync(0xffffffffu, sp[r], 2); t1[r] = __shfl_xor_sync(0xffffffffu, sn[r], 2); }
      if (i < N) {
#pragma unroll
        for (int e = 4; e < 8; e++) {
          ep[cur][e] = ex2(fmaf(p[i][e], L2E, ca[i][(e >> 1) & 1])); en[cur][e] = ex2(fmaf(p[i][e], -L2E, cb[i][(e >> 1) & 1]));
        }
      }
#pragma unroll
      for (int r = 0; r < 2; r++) { rp[r] = rcp(sp[r] + t0[r]); rn[r] = rcp(sn[r] + t1[r]); }
    } else {
#pragma unroll
      for (int e = 0; e < 8; e++) {
        ep[cur][e] = ex2(fmaf(p[i][e], L2E, ca[i][(e >> 1) & 1])); en[cur][e] = ex2(fmaf(p[i][e], -L2E, cb[i][(e >> 1) & 1]));
      }
    }
#pragma unroll
    for (int j = 0; j < 4; j++) {
      if (i < N && j >= 2) {
#pragma unroll
        for (int e = 4 * j; e < 4 * j + 4; e++) {
          ep[cur][e] = ex2(fmaf(p[i][e], L2E, ca[i][(e >> 1) & 1])); en[cur][e] = ex2(fmaf(p[i][e], -L2E, cb[i][(e >> 1) & 1]));
        }
      }
      if (i > 0) {
#pragma unroll
        for (int r = 0; r < 2; r++) {
          pos[i - 1][2 * j + r] = pack_bf16(ep[prv][4 * j + 2 * r] * rp[r], ep[prv][4 * j + 2 * r + 1] * rp[r]);
          neg[i - 1][2 * j + r] = pack_bf16(en[prv][4 * j + 2 * r] * rn[r], en[prv][4 * j + 2 * r + 1] * rn[r]);
        }
      }
    }
  }
}

struct cplx { float r, i; };
__device__ __forceinline__ cplx cmul(cplx a, cplx b) { return {a.r * b.r - a.i * b.i, a.r * b.i + a.i * b.r}; }
__device__ __forceinline__ cplx cfma(cplx a, cplx b, cplx c) {
  return {fmaf(a.r, b.r, fmaf(-a.i, b.i, c.r)), fmaf(a.r, b.i, fmaf(a.i, b.r, c.i))};
}
__device__ __forceinline__ cplx shfl_up_c(cplx v, int d) {
  return {__shfl_up_sync(0xffffffffu, v.r, d, 4), __shfl_up_sync(0xffffffffu, v.i, d, 4)};
}

struct ChanParams { cplx lam, c2; };

__device__ __forceinline__ ChanParams chan_params(float lr, float li, float log_dt) {
  const float dt = __bfloat162float(__float2bfloat16(expf(log_dt)));
  const float mag = expf(dt * lr);
  float sn, cs;
  sincosf(dt * li, &sn, &cs);
  ChanParams c;
  c.lam = {mag * cs, mag * sn};
  const float nr = c.lam.r - 1.0f, ni = c.lam.i;
  const float den = lr * lr + li * li;
  c.c2 = {2.0f * (nr * lr + ni * li) / den, 2.0f * (ni * lr - nr * li) / den};
  return c;
}

__device__ __forceinline__ void epi_bu(float (&are)[64], float (&aim)[64], const ChanParams (&cp)[2],
                                       uint32_t sbase, int G, int chunk, int cw, unsigned epoch) {
  const int lane = threadIdx.x & 31, w = (threadIdx.x & 127) >> 5, q = lane & 3, r8 = lane >> 2;
  cplx E[2] = {{0.f, 0.f}, {0.f, 0.f}};
#pragma unroll
  for (int k8 = 0; k8 < 16; k8++)
#pragma unroll
    for (int e = 0; e < 2; e++)
#pragma unroll
      for (int c = 0; c < 2; c++) E[c] = cfma(cp[c].lam, E[c], cplx{are[4 * k8 + 2 * c + e], aim[4 * k8 + 2 * c + e]});
  TSTAMP(32 + 4 * (threadIdx.x >> 8));
  cplx L32[2], L128[2], prev[2];
#pragma unroll
  for (int c = 0; c < 2; c++) {
    cplx l = cp[c].lam;
#pragma unroll
    for (int s = 0; s < 5; s++) l = cmul(l, l);
    L32[c] = l;
    const cplx l64 = cmul(l, l);
    L128[c] = cmul(l64, l64);
    cplx t = shfl_up_c(E[c], 1);
    if (q >= 1) E[c] = cfma(L32[c], t, E[c]);
    t = shfl_up_c(E[c], 2);
    if (q >= 2) E[c] = cfma(l64, t, E[c]);
    prev[c] = shfl_up_c(E[c], 1);
    if (q == 0) prev[c] = {0.f, 0.f};
  }
  uint4* gE = g_E + (size_t)G * 16 * 64 + 16 * w + r8;
  if (q == 3) {
    st_tagged(gE + chunk * 64, E[0].r, E[0].i, epoch);
    st_tagged(gE + chunk * 64 + 8, E[1].r, E[1].i, epoch);
  }
  cplx V[2][4];
  {
    unsigned long long w0[8], w1[8];
    unsigned pending = 0;
#pragma unroll
    for (int i = 0; i < 8; i++) {
      w0[i] = 0ull; w1[i] = 0ull;
      if (chunk - 1 - 4 * q - (i & 3) >= 0) pending |= 1u << i;
    }
    unsigned spins = 0;
    if (chunk > 0) __nanosleep(600);
    while (true) {
#pragma unroll
      for (int i = 0; i < 8; i++)
        asm volatile("{\n.reg .pred p;\nsetp.ne.u32 p, %3, 0;\n@p ld.relaxed.gpu.global.v2.b64 {%0, %1}, [%2];\n}"
                     : "+l"(w0[i]), "+l"(w1[i]) : "l"(gE + (chunk - 1 - 4 * q - (i & 3)) * 64 + 8 * (i >> 2)), "r"(pending & (1u << i)) : "memory");
#pragma unroll
      for (int i = 0; i < 8; i++)
        if ((unsigned)(w0[i] >> 32) == epoch && (unsigned)(w1[i] >> 32) == epoch) pending &= ~(1u << i);
      if (__all_sync(0xffffffffu, pending == 0)) break;
      __nanosleep(300);
      if (give_up(sbase + OFF_BAR, ++spins)) break;
    }
#pragma unroll
    for (int i = 0; i < 8; i++) V[i >> 2][i & 3] = {__uint_as_float((unsigned)w0[i]), __uint_as_float((unsigned)w1[i])};
  }
  TSTAMP(33 + 4 * (threadIdx.x >> 8));
  cplx s[2];
#pragma unroll
  for (int c = 0; c < 2; c++) {
    cplx Pq = V[c][3];
#pragma unroll
    for (int jj = 2; jj >= 0; jj--) Pq = cfma(L128[c], Pq, V[c][jj]);
    const cplx l256 = cmul(L128[c], L128[c]);
    const cplx l512 = cmul(l256, l256);
    cplx F = {1.f, 0.f};
    cplx G32 = {1.f, 0.f};
    if (q >= 1) { F = l512; G32 = L32[c]; }
    if (q >= 2) { F = cmul(F, l512); G32 = cmul(G32, L32[c]); }
    if (q >= 3) { F = cmul(F, l512); G32 = cmul(G32, L32[c]); }
    Pq = cmul(Pq, F);
#pragma unroll
    for (int o = 1; o <= 2; o <<= 1) {
      Pq.r += __shfl_xor_sync(0xffffffffu, Pq.r, o);
      Pq.i += __shfl_xor_sync(0xffffffffu, Pq.i, o);
    }
    s[c] = cfma(G32, Pq, prev[c]);
  }
  TSTAMP(34 + 4 * (threadIdx.x >> 8));
  if (cw == 1) mbar_wait(sbase + OFF_BAR + B_EBF, 0);
#pragma unroll
  for (int qq = 0; qq < 4; qq++) {
    uint32_t ore[2][4], oim[2][4];
#pragma unroll
    for (int kk = 0; kk < 4; kk++) {
      const int k8 = 4 * qq + kk;
      float hr[2][2], hi[2][2];
#pragma unroll
      for (int e = 0; e < 2; e++)
#pragma unroll
        for (int c = 0; c < 2; c++) {
          s[c] = cfma(cp[c].lam, s[c], cplx{are[4 * k8 + 2 * c + e], aim[4 * k8 + 2 * c + e]});
          hr[c][e] = fmaf(cp[c].c2.r, s[c].r, -cp[c].c2.i * s[c].i);
          hi[c][e] = -fmaf(cp[c].c2.r, s[c].i, cp[c].c2.i * s[c].r);
        }
#pragma unroll
      for (int c = 0; c < 2; c++) {
        ore[c][kk] = pack_bf16(hr[c][0], hr[c][1]);
        oim[c][kk] = pack_bf16(hi[c][0], hi[c][1]);
      }
    }
#pragma unroll
    for (int c = 0; c < 2; c++) {
      const int row = 16 * w + r8 + 8 * c;
      const uint32_t addr = sbase + OFF_PHI + (qq >> 1) * 8192 + row * 128 + ((((qq & 1) * 4 + q) ^ (row & 7)) << 4);
      asm volatile("st.shared.v4.b32 [%0], {%1, %2, %3, %4};" ::"r"(addr), "r"(ore[c][0]), "r"(ore[c][1]), "r"(ore[c][2]), "r"(ore[c][3]) : "memory");
      asm volatile("st.shared.v4.b32 [%0], {%1, %2, %3, %4};" ::"r"(addr + 16384), "r"(oim[c][0]), "r"(oim[c][1]), "r"(oim[c][2]), "r"(oim[c][3]) : "memory");
    }
  }
  TSTAMP(35 + 4 * (threadIdx.x >> 8));
  fence_async_smem();
  wg_bar(1 + cw);
  if ((threadIdx.x & 127) == 0) mbar_arrive(sbase + OFF_BAR + B_JOB + 8 * cw);
}

__device__ __forceinline__ void q_issue_num(float (&num)[20], const uint32_t (&pos)[8], const uint32_t (&neg)[8], uint32_t b) {
  wgmma_fence();
  wgmma_m64n40k16_rs_init<1>(num, pos[0], pos[1], pos[2], pos[3], make_desc(b, 640, 128, 0));
  wgmma_m64n40k16_rs<1>(num, pos[4], pos[5], pos[6], pos[7], make_desc(b + 1280, 640, 128, 0));
  wgmma_m64n40k16_rs<1>(num, neg[0], neg[1], neg[2], neg[3], make_desc(b + 2560, 640, 128, 0));
  wgmma_m64n40k16_rs<1>(num, neg[4], neg[5], neg[6], neg[7], make_desc(b + 3840, 640, 128, 0));
  wgmma_commit();
}
__device__ __forceinline__ void q_store_o(const float (&num)[20], uint32_t rowaddr, int chunk0) {
  const int lane = threadIdx.x & 31, mi = lane >> 3, rin = lane & 7;
  const float d0 = __shfl_sync(0xffffffffu, num[16], lane & ~3), d1 = __shfl_sync(0xffffffffu, num[18], lane & ~3);
  const float i0 = __fdividef(1.0f, d0 + 1e-6f), i1 = __fdividef(1.0f, d1 + 1e-6f);
#pragma unroll
  for (int jp = 0; jp < 2; jp++) {
    const int c0 = chunk0 + jp * 2 + (mi >> 1);
    stmatrix_x4(rowaddr + ((c0 ^ rin) << 4), pack_bf16(num[8 * jp] * i0, num[8 * jp + 1] * i0),
                pack_bf16(num[8 * jp + 2] * i1, num[8 * jp + 3] * i1), pack_bf16(num[8 * jp + 4] * i0, num[8 * jp + 5] * i0),
                pack_bf16(num[8 * jp + 6] * i1, num[8 * jp + 7] * i1));
  }
}
__device__ __forceinline__ void epi_attn(float (&acc0)[64], float (&acc1)[64], uint32_t sbase, int cw, bool isq) {
  const int t = threadIdx.x & 127, lane = t & 31, w = t >> 5, q = lane & 3, r8 = lane >> 2;
  const int mi = lane >> 3, rin = lane & 7;
  const int row0 = w * 16 + (mi & 1) * 8 + rin;
  {
    const uint32_t tile = sbase + OFF_PHI + (isq ? 0 : 16384) + row0 * 128;
#pragma unroll
    for (int j = 0; j < 8; j += 2) {
      const uint32_t addr = tile + (((j + (mi >> 1)) ^ rin) << 4);
      stmatrix_x4(addr, pack_bf16(acc0[4 * j], acc0[4 * j + 1]), pack_bf16(acc0[4 * j + 2], acc0[4 * j + 3]),
                  pack_bf16(acc0[4 * j + 4], acc0[4 * j + 5]), pack_bf16(acc0[4 * j + 6], acc0[4 * j + 7]));
      stmatrix_x4(addr + 8192, pack_bf16(acc1[4 * j], acc1[4 * j + 1]), pack_bf16(acc1[4 * j + 2], acc1[4 * j + 3]),
                  pack_bf16(acc1[4 * j + 4], acc1[4 * j + 5]), pack_bf16(acc1[4 * j + 6], acc1[4 * j + 7]));
    }
  }
#pragma unroll
  for (int j = 8; j < 16; j += 2) {
    const uint32_t aq = sbase + OFF_PHI + 16384 + row0 * 128 + (((j - 8 + (mi >> 1)) ^ rin) << 4);
    const uint32_t av = sbase + OFF_V + ((j - 8) >> 2) * 8192 + row0 * 64 + ((((j & 3) + (mi >> 1)) ^ ((row0 >> 1) & 3)) << 4);
    const uint32_t addr = isq ? aq : av;
    stmatrix_x4(addr, pack_bf16(acc0[4 * j], acc0[4 * j + 1]), pack_bf16(acc0[4 * j + 2], acc0[4 * j + 3]),
                pack_bf16(acc0[4 * j + 4], acc0[4 * j + 5]), pack_bf16(acc0[4 * j + 6], acc0[4 * j + 7]));
    stmatrix_x4(addr + (isq ? 8192 : 4096), pack_bf16(acc1[4 * j], acc1[4 * j + 1]), pack_bf16(acc1[4 * j + 2], acc1[4 * j + 3]),
                pack_bf16(acc1[4 * j + 4], acc1[4 * j + 5]), pack_bf16(acc1[4 * j + 6], acc1[4 * j + 7]));
  }
  fence_async_smem();
  wg_bar(1 + cw);
  TSTAMP(isq ? 56 : 40 + 8 * cw);
  const int nsub = isq ? 2 : 1;
#pragma unroll 1
  for (int sub = 0; sub < nsub; sub++) {
    const int it = 4 * sub;
    (void)it;
    const uint32_t tile = sbase + OFF_PHI + (isq ? sub : 1) * 16384;
    const uint32_t wp = sbase + OFF_WPHI + (isq ? 2 * sub : 2 * cw) * 2048;
    float pq[4][16];
    uint32_t pos[4][8], neg[4][8];
    QT(0);
    wgmma_fence();
#pragma unroll
    for (int i = 0; i < 4; i++) {
      const uint32_t a = tile + (i & 1) * 8192 + (i >> 1) * 64, b = wp + (i >> 1) * 2048;
      wgmma_m64n32k16_ss_init<0, 1>(pq[i], make_desc(a, 16, 1024, 1), make_desc(b, 512, 512, 2));
      wgmma_m64n32k16_ss<0, 1>(pq[i], make_desc(a + 32, 16, 1024, 1), make_desc(b + 1024, 512, 512, 2));
    }
    wgmma_commit();
    wgmma_wait<0>();
#pragma unroll
    for (int i = 0; i < 4; i++) fence_regs(pq[i]);
    QT(1);
    dual_softmax_n<4>(pq, pos, neg);
    QT(2);
    if (!isq) {
      float kvacc[2][20];
      if (cw == 1) mbar_wait(sbase + OFF_BAR + B_EBF + 16, 0);
#pragma unroll
      for (int hh = 0; hh < 2; hh++) {
#pragma unroll
        for (int half = 0; half < 2; half++) {
          const uint32_t rb = sbase + OFF_PHI + hh * 16384 + (half * 64 + row0) * 128;
#pragma unroll
          for (int jp = 0; jp < 2; jp++) {
            const int c0 = jp * 2 + (mi >> 1), i = 2 * hh + half;
            stmatrix_x4(rb + ((c0 ^ rin) << 4), pos[i][4 * jp], pos[i][4 * jp + 1], pos[i][4 * jp + 2], pos[i][4 * jp + 3]);
            stmatrix_x4(rb + (((c0 + 4) ^ rin) << 4), neg[i][4 * jp], neg[i][4 * jp + 1], neg[i][4 * jp + 2], neg[i][4 * jp + 3]);
          }
        }
      }
      fence_async_smem();
      wg_bar(1 + cw);
      wgmma_fence();
#pragma unroll
      for (int hh = 0; hh < 2; hh++)
#pragma unroll
        for (int ks = 0; ks < 8; ks++) {
          const uint32_t vb = sbase + OFF_V + hh * 8192 + ks * 1024;
          const uint64_t da = make_desc(sbase + OFF_PHI + hh * 16384 + ks * 2048, 1024, 1024, 1);
          const uint64_t db = make_desc(vb, sbase + OFF_ONES - vb, 512, 2);
          if (ks == 0) wgmma_m64n40k16_ss_init<1, 1>(kvacc[hh], da, db);
          else wgmma_m64n40k16_ss<1, 1>(kvacc[hh], da, db);
        }
      wgmma_commit();
      TSTAMP(42 + 8 * cw);
      wgmma_wait<0>();
      fence_regs(kvacc[0]);
      fence_regs(kvacc[1]);
      TSTAMP(43 + 8 * cw);
      wg_bar(1 + cw);
      if (t == 0) mbar_arrive(sbase + OFF_BAR + B_EBA + 8 * cw);
#pragma unroll
      for (int hh = 0; hh < 2; hh++) {
#pragma unroll
        for (int rr = 0; rr < 2; rr++) {
          const int off = ((16 * w + r8 + 8 * rr) * KVW + 2 * q) * 4;
#pragma unroll
          for (int j = 0; j < 5; j++) {
            const int o = off + 32 * j;
            const uint32_t dst = (hh == 0) ? sbase + OFF_PHI + o
                                           : (o < 6144 ? sbase + OFF_PHI + 10240 + o : sbase + OFF_V + 16384 - 6144 + o);
            asm volatile("st.shared.v2.f32 [%0], {%1, %2};" ::"r"(dst), "f"(kvacc[hh][4 * j + 2 * rr]), "f"(kvacc[hh][4 * j + 2 * rr + 1]) : "memory");
          }
        }
      }
      fence_async_smem();
      wg_bar(1 + cw);
      if (t == 0) mbar_arrive(sbase + OFF_BAR + B_JOB + 16 + 8 * cw);
      TSTAMP(44 + 8 * cw);
    } else {
      float num[4][20];
      mbar_wait(sbase + OFF_BAR + B_KVX + 8 * sub, 0);
      TSTAMP(57 + sub);
      QT(3);
#pragma unroll
      for (int i = 0; i < 4; i++) q_issue_num(num[i], pos[i], neg[i], sbase + OFF_V + (2 * sub + (i >> 1)) * 5120);
      QT(4);
      wgmma_wait<2>();
      fence_regs(num[0]); fence_regs(num[1]);
      QT(5);
      q_store_o(num[0], tile + row0 * 128, 0);
      q_store_o(num[1], tile + 8192 + row0 * 128, 0);
      wgmma_wait<0>();
      fence_regs(num[2]); fence_regs(num[3]);
      QT(6);
      q_store_o(num[2], tile + row0 * 128, 4);
      q_store_o(num[3], tile + 8192 + row0 * 128, 4);
      QT(7);
      fence_async_smem();
      wg_bar(1);
      if (t == 0) mbar_arrive(sbase + OFF_BAR + B_JOB + 32 + 8 * sub);
    }
  }
}

__device__ __forceinline__ void helper_kv(uint32_t sbase, int g, unsigned epoch) {
  const int h = threadIdx.x - 64;
  mbar_wait_long(sbase + OFF_BAR + B_EBA + 8, 0);
#pragma unroll 1
  for (int pr = 0; pr < 2; pr++) {
    if ((h & 31) == 0) {
      wait_ge(sbase + OFF_BAR, &g_flags.kvcnt[(g + 8 * pr) * 8], 16u * epoch);
    }
    __syncwarp();
    const float4* src = reinterpret_cast<const float4*>(g_kv + (size_t)(2 * g + 16 * pr) * 64 * KVW);
#pragma unroll 1
    for (int ib = 0; ib < 3; ib++) {
      float4 u[7];
#pragma unroll
      for (int i = 0; i < 7; i++) u[i] = __ldcg(src + min((ib * 7 + i) * 64 + h, 1279));
#pragma unroll
      for (int i = 0; i < 7; i++) {
        const int idx = min((ib * 7 + i) * 64 + h, 1279);
        const int f2 = idx / 10, j = idx - f2 * 10;
        const uint32_t dst = sbase + OFF_V + pr * 10240 + (f2 >> 3) * 640 + (j >> 1) * 128 + (f2 & 7) * 16 + (j & 1) * 8;
        asm volatile("st.shared.v2.b32 [%0], {%1, %2};" ::"r"(dst), "r"(pack_bf16(u[i].x, u[i].y)), "r"(pack_bf16(u[i].z, u[i].w)) : "memory");
      }
    }
    fence_async_smem();
    __syncwarp();
    if ((h & 31) == 0) mbar_arrive(sbase + OFF_BAR + B_KVX + 8 * pr);
  }
}

__device__ __forceinline__ void store_agent(const Params& prm, uint32_t sbase, int g, int rb, unsigned epoch) {
  const uint32_t bars = sbase + OFF_BAR;
#pragma unroll 1
  for (int j = 0; j < 6; j++) {
    mbar_wait_long(bars + B_JOB + 8 * j, 0);
    unsigned* flag;
    if (j < 2) {
      const int G = g + 8 * j;
#pragma unroll 1
      for (int u = 0; u < 16; u++) {
        tma_store_3d(&prm.tmHTs, sbase + OFF_PHI + u * 2048, 0, (u >> 3) * 1024 + 64 * G + (u & 3) * 16, 2 * rb + ((u >> 2) & 1));
        __nanosleep(50);
      }
      flag = &g_flags.hcnt[rb * 8];
    } else if (j < 4) {
      const int hp = g + 8 * (j - 2);
      wait_ge(bars, &g_flags.zero_cnt, 128u * epoch);
      fence_async_global();
#pragma unroll 1
      for (int u = 0; u < 10; u++) {
        const uint32_t o = u * 2048;
        const uint32_t src = (o < 16384) ? sbase + OFF_PHI + o : sbase + OFF_V + o;
        bulk_reduce_f32(g_kv + (size_t)(2 * hp) * 64 * KVW + o / 4, src, 2048);
        __nanosleep(50);
      }
      flag = &g_flags.kvcnt[hp * 8];
    } else {
      tma_store_2d(&prm.tmO, sbase + OFF_PHI + (j - 4) * 16384, 64 * (g + 8 * (j - 4)), 128 * rb);
      flag = &g_flags.ocnt[(2 * rb + (j - 4)) * 8];
    }
    bulk_commit();
    if (j != 4) {
      bulk_wait_read();
      mbar_arrive(bars + B_EBF + 8 * (j < 4 ? j : 4));
    }
    bulk_wait_all();
    red_relaxed_add(flag, 1);
  }
}

constexpr int OST = 544;
__device__ __forceinline__ void stage_half(const float (&a)[64], uint32_t wbuf) {
  const int lane = threadIdx.x & 31, q = lane & 3, r8 = lane >> 2;
#pragma unroll
  for (int j = 0; j < 16; j++) {
    asm volatile("st.shared.v2.f32 [%0], {%1, %2};" ::"r"(wbuf + r8 * OST + j * 32 + q * 8), "f"(a[4 * j]), "f"(a[4 * j + 1]) : "memory");
    asm volatile("st.shared.v2.f32 [%0], {%1, %2};" ::"r"(wbuf + (r8 + 8) * OST + j * 32 + q * 8), "f"(a[4 * j + 2]), "f"(a[4 * j + 3]) : "memory");
  }
  __syncwarp();
}
__device__ __forceinline__ float4 lds128(uint32_t addr) {
  float4 v;
  asm volatile("ld.shared.v4.f32 {%0, %1, %2, %3}, [%4];" : "=f"(v.x), "=f"(v.y), "=f"(v.z), "=f"(v.w) : "r"(addr) : "memory");
  return v;
}
__device__ __forceinline__ void store_y(float (&acc0)[64], const float (&acc1)[64], uint32_t wbuf, const Params& prm, int rb, int g) {
  const int lane = threadIdx.x & 31, w = (threadIdx.x & 127) >> 5;
  const uint2 dk = __ldg(reinterpret_cast<const uint2*>(prm.dskip + 128 * g) + lane);
#pragma unroll 1
  for (int half = 0; half < 2; half++) {
    const int m0 = 64 * half + 16 * w;
    const int t0 = rb * 128 + 32 * ((m0 >> 3) & 3) + 8 * (m0 >> 5);
    uint2 xs[16];
#pragma unroll
    for (int r = 0; r < 16; r++)
      xs[r] = __ldg(reinterpret_cast<const uint2*>(prm.xB + (size_t)(t0 + (r & 7) + (r >> 3) * 32) * DM + 128 * g) + lane);
    stage_half(acc0, wbuf);
    float* dst = prm.out + (size_t)t0 * 2048 + 1024 + 128 * g + 4 * lane;
#pragma unroll
    for (int r = 0; r < 16; r++) {
      float4 v = lds128(wbuf + r * OST + lane * 16);
      const float2 s0 = __bfloat1622float2(__hmul2(*reinterpret_cast<const __nv_bfloat162*>(&xs[r].x), *reinterpret_cast<const __nv_bfloat162*>(&dk.x)));
      const float2 s1 = __bfloat1622float2(__hmul2(*reinterpret_cast<const __nv_bfloat162*>(&xs[r].y), *reinterpret_cast<const __nv_bfloat162*>(&dk.y)));
      v.x += s0.x; v.y += s0.y; v.z += s1.x; v.w += s1.y;
      __stcs(reinterpret_cast<float4*>(dst + (size_t)((r & 7) + (r >> 3) * 32) * 2048), v);
    }
    __syncwarp();
#pragma unroll
    for (int i = 0; i < 64; i++) acc0[i] = acc1[i];
  }
}
__device__ __forceinline__ void drain_out(uint32_t wbuf, float* dst  ) {
  const int lane = threadIdx.x & 31;
#pragma unroll
  for (int r = 0; r < 16; r++) {
    const float4 v = lds128(wbuf + r * OST + lane * 16);
    const uint32_t p0 = pack_bf16(v.x, v.y), p1 = pack_bf16(v.z, v.w);
    __stcs(reinterpret_cast<float4*>(dst + (size_t)r * 2048) + lane,
           make_float4(__uint_as_float(p0 << 16), __uint_as_float(p0 & 0xffff0000u), __uint_as_float(p1 << 16), __uint_as_float(p1 & 0xffff0000u)));
  }
}

__global__ void __launch_bounds__(384, 1) fused_kernel(const __grid_constant__ Params prm) {
  extern __shared__ uint8_t smem_raw[];
  const uint32_t sbase = (smem_u32(smem_raw) + 1023) & ~1023u;
  const uint32_t bars = sbase + OFF_BAR;
  const int tid = threadIdx.x, wg = __shfl_sync(0xffffffffu, tid >> 7, 0);
  const int cl = blockIdx.x >> 1, rank = blockIdx.x & 1;
  const int g = cl >> 3, rb = 2 * (cl & 7) + rank;

  if (tid == 0) {
    for (int s = 0; s < STAGES; s++) { mbar_init(bars + 8 * s, 1);
      mbar_init(bars + B_EMPTY + 8 * s, 8);
    }
    mbar_init(bars + B_ORD, 1); mbar_init(bars + B_ORD + 8, 1); mbar_init(bars + B_WPHI, 1); mbar_init(bars + B_EPOCH, 1); mbar_init(bars + B_KVX, 2); mbar_init(bars + B_KVX + 8, 2);
    for (int j = 0; j < 6; j++) mbar_init(bars + B_JOB + 8 * j, 1);
    mbar_init(bars + B_PARAM, 2); mbar_init(bars + B_EBA, 1); mbar_init(bars + B_EBA + 8, 1);
    for (int j = 0; j < 5; j++) mbar_init(bars + B_EBF + 8 * j, 1);
    asm volatile("st.shared.u32 [%0], %1;" ::"r"(bars + B_DEAD), "r"(0u) : "memory");
    asm volatile("fence.mbarrier_init.release.cluster;" ::: "memory");
    asm volatile("fence.proxy.async.shared::cta;" ::: "memory");
#pragma unroll 1
    for (int kb = 0; kb < STAGES; kb++) {
      const uint32_t full = bars + 8 * kb, sw = sbase + kb * STAGE_BYTES;
      mbar_expect_tx(full, STAGE_BYTES);
      tma_5d(sw + 16384, &prm.tmXB, kb * 64, 0, 0, 0, rb, full);
      tma_2d(sw, &prm.tmBre, kb * 64, 64 * g, full);
      tma_2d(sw + 8192, &prm.tmBim, kb * 64, 64 * g, full);
    }
  } else if (tid == 32) {
    prefetch_tm(&prm.tmXB); prefetch_tm(rank ? &prm.tmBim : &prm.tmBre); prefetch_tm(&prm.tmWphi);
    prefetch_tm(&prm.tmXA); prefetch_tm(&prm.tmWqkv); prefetch_tm(&prm.tmHT);
    prefetch_tm(&prm.tmCre); prefetch_tm(&prm.tmCim); prefetch_tm(&prm.tmO); prefetch_tm(&prm.tmWo);
  } else if (tid >= 64 && tid < 128) {
    asm volatile("st.shared.v4.b32 [%0], {%1, %2, %2, %2};" ::"r"(sbase + OFF_ONES + (tid - 64) * 16), "r"(0x00003F80u), "r"(0u) : "memory");
    fence_async_smem();
  }
  __syncthreads();
  asm volatile("barrier.cluster.arrive.relaxed.aligned;\nbarrier.cluster.wait.acquire.aligned;" ::: "memory");

  if (wg == 0) {
    reg_dealloc<56>();
    const int warp = __shfl_sync(0xffffffffu, tid >> 5, 0), lane = tid & 31;
    if (warp == 0) {
      const bool leader = elect_one();
      TSTAMP(0);
      if (leader) {
        mbar_expect_tx(bars + B_WPHI, 8192);
        tma_2d(sbase + OFF_WPHI, &prm.tmWphi, 0, 64 * g, bars + B_WPHI);
        tma_2d(sbase + OFF_WPHI + 4096, &prm.tmWphi, 0, 64 * g + 512, bars + B_WPHI);
      }
      int stage = 0;
      uint32_t phase = 0;
      unsigned epoch = 0;
      auto run = [&](auto kind, const CUtensorMap* tw, int w0, const CUtensorMap* tx, int kb0, int kb1) {
        constexpr int KIND = decltype(kind)::value;
#pragma unroll 1
        for (int kb = kb0; kb < kb1; kb++) {
          mbar_wait(bars + B_EMPTY + 8 * stage, phase);
          if (leader) {
            const uint32_t full = bars + 8 * stage;
            const uint32_t sw = sbase + stage * STAGE_BYTES;
            mbar_expect_tx(full, STAGE_BYTES);
            if (KIND == 0) {
              tma_2d_mc(sw + rank * 8192, tw, kb * 64, w0, full);
              tma_5d(sw + 16384, tx, kb * 64, 0, 0, 0, rb, full);
            } else if (KIND == 1) {
              tma_2d_mc(sw + rank * 8192, tw, w0, kb * 64, full);
              tma_2d(sw + 16384, tx, kb * 64, rb * 128, full);
            } else {
              tma_2d_mc(sw + rank * 8192, tw, (kb & 15) * 64, w0, full);
              tma_3d(sw + 16384, tx, 0, kb * 64, 2 * rb, full);
            }
          }
          if (++stage == STAGES) { stage = 0; phase ^= 1; }
        }
      };
      using K0 = std::integral_constant<int, 0>;
      using K1 = std::integral_constant<int, 1>;
      using K2 = std::integral_constant<int, 2>;
#pragma unroll 1
      for (int i = 0; i < 2; i++) run(K0{}, rank ? &prm.tmBim : &prm.tmBre, 64 * (g + 8 * i), &prm.tmXB, i == 0 ? STAGES : 0, 16);
#pragma unroll 1
      for (int i = 0; i < 3; i++)
        run(K1{}, &prm.tmWqkv, i < 2 ? 1024 + rank * 1024 + 64 * (g + 8 * i) : 64 * (g + 8 * rank), &prm.tmXA, 0, 16);
      mbar_wait(bars + B_EPOCH, 0);
      asm volatile("ld.shared.u32 %0, [%1];" : "=r"(epoch) : "r"(bars + B_EPOCHV) : "memory");
      wait_ge(bars, &g_flags.hcnt[rb * 8], 16u * epoch);
      fence_async_global();
#pragma unroll 1
      for (int i = 0; i < 2; i++) run(K2{}, i ? &prm.tmCim : &prm.tmCre, 128 * g + 64 * rank, &prm.tmHT, 16 * i, 16 * i + 16);
#pragma unroll 1
      for (int i = 0; i < 2; i++) {
        wait_ge(bars, &g_flags.ocnt[(2 * rb + i) * 8], 8u * epoch);
        fence_async_global();
        run(K1{}, &prm.tmWo, 128 * g + 64 * rank, &prm.tmO, 8 * i, 8 * i + 8);
      }
      TSTAMP(1);
    } else if (warp == 1) {
      unsigned epoch = 0;
      if (lane == 0) {
        epoch = (atomicAdd(&g_flags.ticket, 1u) >> 7) + 1u;
        asm volatile("st.shared.u32 [%0], %1;" ::"r"(bars + B_EPOCHV), "r"(epoch) : "memory");
        mbar_arrive(bars + B_EPOCH);
      }
      uint4* z = reinterpret_cast<uint4*>(g_kv) + blockIdx.x * 160;
#pragma unroll
      for (int i = 0; i < 5; i++) __stcg(z + i * 32 + lane, make_uint4(0, 0, 0, 0));
      __syncwarp();
      if (lane == 0) {
        red_release_add(&g_flags.zero_cnt, 1);
        store_agent(prm, sbase, g, rb, epoch);
      }
    } else {
#pragma unroll 1
      for (int c = 0; c < 2; c++) {
        const int ch = tid - 64, p = 64 * (g + 8 * c) + ch;
        const ChanParams cp = chan_params(__bfloat162float(prm.lam_re[p]), __bfloat162float(prm.lam_im[p]), __bfloat162float(prm.log_dt[p]));
        asm volatile("st.shared.v4.f32 [%0], {%1, %2, %3, %4};" ::"r"(sbase + OFF_V + (c * 64 + ch) * 16), "f"(cp.lam.r), "f"(cp.lam.i),
                     "f"(cp.c2.r), "f"(cp.c2.i) : "memory");
      }
      __syncwarp();
      if (lane == 0) mbar_arrive(bars + B_PARAM);
      unsigned epoch;
      mbar_wait(bars + B_EPOCH, 0);
      asm volatile("ld.shared.u32 %0, [%1];" : "=r"(epoch) : "r"(bars + B_EPOCHV) : "memory");
      helper_kv(sbase, g, epoch);
    }
    __syncwarp();
    asm volatile("barrier.cluster.arrive.relaxed.aligned;\nbarrier.cluster.wait.aligned;" ::: "memory");
  } else {
    reg_alloc<224>();
    const int cw = wg - 1;
    const int t = tid & 127, lane = t & 31, w = t >> 5, r8 = lane >> 2;
    float acc0[64], acc1[64];
    unsigned epoch;
    {
      const int G = g + 8 * cw;
      ChanParams cp[2];
      TSTAMP(2 + 12 * cw);
      mainloop<0>(acc0, acc1, 16 * cw, 16, sbase, cw, cw ^ 1);
      TSTAMP(3 + 12 * cw);
      mbar_wait(bars + B_PARAM, 0);
#pragma unroll
      for (int c = 0; c < 2; c++) {
        const float4 v = lds128(sbase + OFF_V + (cw * 64 + 16 * w + r8 + 8 * c) * 16);
        cp[c].lam = {v.x, v.y};
        cp[c].c2 = {v.z, v.w};
      }
      mbar_wait(bars + B_EPOCH, 0);
      asm volatile("ld.shared.u32 %0, [%1];" : "=r"(epoch) : "r"(bars + B_EPOCHV) : "memory");
      epi_bu(acc0, acc1, cp, sbase, G, rb, cw, epoch);
      TSTAMP(4 + 12 * cw);
    }
#pragma unroll 1
    for (int step = 0; step < 3; step++) {
      const int it0 = cw ? 48 : (step == 0 ? 32 : (step == 1 ? 64 : 112));
      mainloop<1>(acc0, acc1, it0, 16, sbase, cw, cw ? 1 : (step & 1));
      TSTAMP(step == 0 ? 5 + 12 * cw : (step == 1 ? 7 : 9));
      if (step == 2) {
        stage_half(acc1, sbase + (4 + w) * 16 * OST);
        asm volatile("bar.arrive 3, 256;" ::: "memory");
        stage_half(acc0, sbase + w * 16 * OST);
        drain_out(sbase + w * 16 * OST, prm.out + (size_t)(rb * 128 + 16 * w) * 2048 + 128 * g);
        TSTAMP(10);
        break;
      }
      mbar_wait(bars + B_WPHI, 0);
      if (cw == 1) {
        mbar_wait(bars + B_EBA, 0);
      } else {
        if (step == 1) mbar_wait(bars + B_EBA + 8, 0);
        mbar_wait(bars + B_EBF + (step == 0 ? 8 : 24), 0);
      }
      epi_attn(acc0, acc1, sbase, cw, step == 1);
      TSTAMP(step == 0 ? 6 + 12 * cw : 8);
      if (cw == 1) break;
    }
    if (cw == 1) {
      mainloop<2>(acc0, acc1, 80, 32, sbase, 1, 0);
      TSTAMP(19);
      mbar_wait(bars + B_EBF + 32, 0);
      store_y(acc0, acc1, sbase + OFF_EB + w * 16 * OST, prm, rb, g);
      TSTAMP(20);
      asm volatile("bar.sync 3, 256;" ::: "memory");
      drain_out(sbase + (4 + w) * 16 * OST, prm.out + (size_t)(rb * 128 + 64 + 16 * w) * 2048 + 128 * g);
    }
    asm volatile("barrier.cluster.arrive.relaxed.aligned;\nbarrier.cluster.wait.aligned;" ::: "memory");
  }
}

typedef CUresult (*PFN_encodeTiled)(CUtensorMap*, CUtensorMapDataType, cuuint32_t, void*, const cuuint64_t*, const cuuint64_t*,
                                    const cuuint32_t*, const cuuint32_t*, CUtensorMapInterleave, CUtensorMapSwizzle,
                                    CUtensorMapL2promotion, CUtensorMapFloatOOBfill);

bool make_tm(PFN_encodeTiled enc, CUtensorMap* tm, const void* base, int rank, const uint64_t* dims, const uint64_t* strides,
             const uint32_t* box, CUtensorMapSwizzle sw) {
  cuuint64_t gd[5], gs[5];
  cuuint32_t bx[5], es[5];
  for (int i = 0; i < rank; i++) { gd[i] = dims[i]; bx[i] = box[i]; es[i] = 1; }
  for (int i = 0; i + 1 < rank; i++) gs[i] = strides[i];
  return enc(tm, CU_TENSOR_MAP_DATA_TYPE_BFLOAT16, rank, const_cast<void*>(base), gd, gs, bx, es, CU_TENSOR_MAP_INTERLEAVE_NONE, sw,
             CU_TENSOR_MAP_L2_PROMOTION_L2_256B, CU_TENSOR_MAP_FLOAT_OOB_FILL_NONE) == CUDA_SUCCESS;
}
bool make_tm2(PFN_encodeTiled enc, CUtensorMap* tm, const void* base, uint64_t inner, uint64_t outer, uint32_t b0, uint32_t b1,
              CUtensorMapSwizzle sw = CU_TENSOR_MAP_SWIZZLE_128B) {
  const uint64_t dims[2] = {inner, outer}, str[1] = {inner * 2};
  const uint32_t box[2] = {b0, b1};
  return make_tm(enc, tm, base, 2, dims, str, box, sw);
}

}

extern "C" void kernel_launch(void* const* d_in, const int* in_sizes, int n_in, void* d_out, int out_size) {
  (void)in_sizes; (void)n_in; (void)out_size;
  static PFN_encodeTiled enc = nullptr;
  static void *pHT = nullptr, *pO = nullptr;
  if (!enc) {
    void* fn = nullptr;
    cudaDriverEntryPointQueryResult qr;
    if (cudaGetDriverEntryPoint("cuTensorMapEncodeTiled", &fn, cudaEnableDefault, &qr) != cudaSuccess || !fn) return;
    enc = (PFN_encodeTiled)fn;
    cudaFuncSetAttribute(fused_kernel, cudaFuncAttributeMaxDynamicSharedMemorySize, SMEM_BYTES);
    cudaGetSymbolAddress(&pHT, g_HT);
    cudaGetSymbolAddress(&pO, g_O);
  }
  Params prm;
  bool ok = true;
  {
    const uint64_t dims[5] = {1024, 2, 4, 16, 16}, str[4] = {2048, 65536, 4096, 262144};
    const uint32_t box[5] = {64, 2, 4, 16, 1};
    ok &= make_tm(enc, &prm.tmXB, d_in[4], 5, dims, str, box, CU_TENSOR_MAP_SWIZZLE_128B);
  }
  ok &= make_tm2(enc, &prm.tmBre, d_in[7], 1024, 1024, 64, 64);
  ok &= make_tm2(enc, &prm.tmBim, d_in[8], 1024, 1024, 64, 64);
  ok &= make_tm2(enc, &prm.tmXA, d_in[0], 1024, 2048, 64, 128);
  ok &= make_tm2(enc, &prm.tmWqkv, d_in[1], 3072, 1024, 64, 64);
  ok &= make_tm2(enc, &prm.tmWphi, d_in[2], 32, 1024, 32, 64, CU_TENSOR_MAP_SWIZZLE_64B);
  {
    const uint64_t dims[3] = {64, 2048, 32}, str[2] = {4096, 128};
    const uint32_t box[3] = {64, 64, 2};
    ok &= make_tm(enc, &prm.tmHT, pHT, 3, dims, str, box, CU_TENSOR_MAP_SWIZZLE_128B);
  }
  {
    const uint64_t dims[3] = {64, 2048, 32}, str[2] = {4096, 128};
    const uint32_t box[3] = {64, 16, 1};
    ok &= make_tm(enc, &prm.tmHTs, pHT, 3, dims, str, box, CU_TENSOR_MAP_SWIZZLE_128B);
  }
  ok &= make_tm2(enc, &prm.tmCre, d_in[9], 1024, 1024, 64, 64);
  ok &= make_tm2(enc, &prm.tmCim, d_in[10], 1024, 1024, 64, 64);
  ok &= make_tm2(enc, &prm.tmO, pO, 1024, 2048, 64, 128);
  ok &= make_tm2(enc, &prm.tmWo, d_in[3], 1024, 1024, 64, 64);
  if (!ok) return;
  prm.xB = (const __nv_bfloat16*)d_in[4];
  prm.lam_re = (const __nv_bfloat16*)d_in[5];
  prm.lam_im = (const __nv_bfloat16*)d_in[6];
  prm.log_dt = (const __nv_bfloat16*)d_in[11];
  prm.dskip = (const __nv_bfloat16*)d_in[12];
  prm.out = (float*)d_out;

  cudaLaunchConfig_t cfg = {};
  cfg.gridDim = dim3(128);
  cfg.blockDim = dim3(384);
  cfg.dynamicSmemBytes = SMEM_BYTES;
  cfg.stream = cudaStreamPerThread;
  cudaLaunchAttribute attr[1];
  attr[0].id = cudaLaunchAttributeClusterDimension;
  attr[0].val.clusterDim.x = 2; attr[0].val.clusterDim.y = 1; attr[0].val.clusterDim.z = 1;
  cfg.attrs = attr;
  cfg.numAttrs = 1;
  cudaLaunchKernelEx(&cfg, fused_kernel, prm);
}
```

```cpp
#include <cuda_runtime.h>
#include <cuda_bf16.h>
#include <cuda.h>
#include <stdint.h>
#include <type_traits>

#define HANDOFF 1
#define PACE_KV3 0
#define PACE_HT 50
#define PACE_KV 50
#define STOUT __stcs
namespace {

constexpr int SEQ = 2048;
constexpr int DM = 1024;
#define NSTAGES 5
constexpr int STAGES = NSTAGES;
constexpr int STAGE_BYTES = 32768;
constexpr int OFF_EB = 5 * STAGE_BYTES;
constexpr int OFF_PHI = OFF_EB;
constexpr int OFF_V = OFF_EB + 32768;
constexpr int OFF_WPHI = OFF_EB + 53248;
constexpr int OFF_ONES = OFF_EB + 61440;
constexpr int OFF_BAR = OFF_EB + 62464;
constexpr int SMEM_BYTES = OFF_BAR + 512 + 1024;
constexpr int B_EMPTY = 64, B_ORD = 128  , B_WPHI = 144, B_EPOCH = 152, B_PARAM = 160, B_KVX = 168  , B_EBA = 184  ,
              B_EPOCHV = 200, B_DEAD = 204, B_JOB = 208  , B_EBF = 256  ;

constexpr int KVW = 40;

struct Params {
  CUtensorMap tmXB;
  CUtensorMap tmBre, tmBim;
  CUtensorMap tmXA;
  CUtensorMap tmWqkv;
  CUtensorMap tmWphi;
  CUtensorMap tmHT;
  CUtensorMap tmHTs;
  CUtensorMap tmCre, tmCim;
  CUtensorMap tmO;
  CUtensorMap tmWo;
  const __nv_bfloat16* xB;
  const __nv_bfloat16* lam_re;
  const __nv_bfloat16* lam_im;
  const __nv_bfloat16* log_dt;
  const __nv_bfloat16* dskip;
  float* out;
};

__device__ __nv_bfloat16 g_HT[2048 * 2048];
__device__ __nv_bfloat16 g_O[SEQ * DM];
__device__ float g_kv[32 * 64 * KVW];
__device__ uint4 g_E[16 * 16 * 64];
struct Flags {
  unsigned ticket;   unsigned pad0[31];
  unsigned zero_cnt; unsigned pad1[31];
  unsigned hcnt[16 * 8];
  unsigned kvcnt[16 * 8];
  unsigned ocnt[2 * 16 * 8];
};
__device__ Flags g_flags;

__device__ __forceinline__ uint32_t smem_u32(const void* p) { return (uint32_t)__cvta_generic_to_shared(p); }
__device__ __forceinline__ void mbar_init(uint32_t bar, uint32_t count) {
  asm volatile("mbarrier.init.shared::cta.b64 [%0], %1;" ::"r"(bar), "r"(count));
}
__device__ __forceinline__ void mbar_expect_tx(uint32_t bar, uint32_t bytes) {
  asm volatile("mbarrier.arrive.expect_tx.shared::cta.b64 _, [%0], %1;" ::"r"(bar), "r"(bytes) : "memory");
}
__device__ __forceinline__ void mbar_arrive(uint32_t bar) {
  asm volatile("mbarrier.arrive.shared::cta.b64 _, [%0];" ::"r"(bar) : "memory");
}
__device__ __forceinline__ void mbar_arrive_cluster(uint32_t bar, uint32_t cta) {
  asm volatile("{\n.reg .b32 ra;\nmapa.shared::cluster.u32 ra, %0, %1;\nmbarrier.arrive.shared::cluster.b64 _, [ra];\n}" ::"r"(bar), "r"(cta) : "memory");
}
__device__ __forceinline__ uint32_t dead_addr(uint32_t bar) { return (bar & ~0x1FFu) + B_DEAD; }
__device__ __forceinline__ void mbar_wait(uint32_t bar, uint32_t parity) {
  asm volatile(
      "{\n.reg .pred p;\n.reg .u32 c, d;\n"
      "mov.u32 c, 0;\n"
      "WAIT_LOOP:\n"
      "mbarrier.try_wait.parity.shared::cta.b64 p, [%0], %1;\n"
      "@p bra WAIT_DONE;\n"
      "add.u32 c, c, 1;\n"
      "setp.gt.u32 p, c, 0x200000;\n"
      "@p st.volatile.shared.u32 [%2], c;\n"
      "ld.volatile.shared.u32 d, [%2];\n"
      "setp.eq.u32 p, d, 0;\n"
      "@p bra WAIT_LOOP;\n"
      "WAIT_DONE:\n}\n" ::"r"(bar), "r"(parity), "r"(dead_addr(bar)) : "memory");
}
__device__ __forceinline__ void mbar_wait_long(uint32_t bar, uint32_t parity) {
  asm volatile(
      "{\n.reg .pred p;\n.reg .u32 c, d;\n"
      "mov.u32 c, 0;\n"
      "WAITL_LOOP:\n"
      "mbarrier.try_wait.parity.shared::cta.b64 p, [%0], %1;\n"
      "@p bra WAITL_DONE;\n"
      "nanosleep.u32 100;\n"
      "add.u32 c, c, 1;\n"
      "setp.gt.u32 p, c, 0x200000;\n"
      "@p st.volatile.shared.u32 [%2], c;\n"
      "ld.volatile.shared.u32 d, [%2];\n"
      "setp.eq.u32 p, d, 0;\n"
      "@p bra WAITL_LOOP;\n"
      "WAITL_DONE:\n}\n" ::"r"(bar), "r"(parity), "r"(dead_addr(bar)) : "memory");
}
__device__ __forceinline__ bool give_up(uint32_t bars, unsigned spins) {
  unsigned d;
  if (spins > (1u << 20)) asm volatile("st.volatile.shared.u32 [%0], %1;" ::"r"(bars + B_DEAD), "r"(spins) : "memory");
  asm volatile("ld.volatile.shared.u32 %0, [%1];" : "=r"(d) : "r"(bars + B_DEAD) : "memory");
  return d != 0;
}
__device__ __forceinline__ unsigned ld_relaxed(const unsigned* p) {
  unsigned v;
  asm volatile("ld.relaxed.gpu.global.u32 %0, [%1];" : "=r"(v) : "l"(p) : "memory");
  return v;
}
__device__ __forceinline__ void wait_ge(uint32_t bars, const unsigned* p, unsigned target) {
  unsigned spins = 0;
  while ((int)(ld_relaxed(p) - target) < 0) {
    __nanosleep(128);
    if (give_up(bars, ++spins)) break;
  }
  asm volatile("{\n.reg .u32 v;\nld.acquire.gpu.global.u32 v, [%0];\n}" ::"l"(p) : "memory");
}
__device__ __forceinline__ void red_release_add(unsigned* p, unsigned v) {
  asm volatile("red.release.gpu.global.add.u32 [%0], %1;" ::"l"(p), "r"(v) : "memory");
}
__device__ __forceinline__ void red_relaxed_add(unsigned* p, unsigned v) {
  asm volatile("red.relaxed.gpu.global.add.u32 [%0], %1;" ::"l"(p), "r"(v) : "memory");
}
__device__ __forceinline__ void st_tagged(uint4* p, float a, float b, unsigned tag) {
  const unsigned long long w0 = ((unsigned long long)tag << 32) | __float_as_uint(a);
  const unsigned long long w1 = ((unsigned long long)tag << 32) | __float_as_uint(b);
  asm volatile("st.relaxed.gpu.global.v2.b64 [%0], {%1, %2};" ::"l"(p), "l"(w0), "l"(w1) : "memory");
}
__device__ __forceinline__ void bulk_commit() { asm volatile("cp.async.bulk.commit_group;" ::: "memory"); }
__device__ __forceinline__ void bulk_wait_read() { asm volatile("cp.async.bulk.wait_group.read 0;" ::: "memory"); }
__device__ __forceinline__ void bulk_wait_all() { asm volatile("cp.async.bulk.wait_group 0;" ::: "memory"); }
__device__ __forceinline__ void bulk_reduce_f32(float* dst, uint32_t src, uint32_t bytes) {
  asm volatile("cp.reduce.async.bulk.global.shared::cta.bulk_group.add.f32 [%0], [%1], %2;" ::"l"(dst), "r"(src), "r"(bytes) : "memory");
}
__device__ __forceinline__ void tma_store_3d(const CUtensorMap* tm, uint32_t src, int c0, int c1, int c2) {
  asm volatile("cp.async.bulk.tensor.3d.global.shared::cta.bulk_group [%0, {%2, %3, %4}], [%1];"
               ::"l"(tm), "r"(src), "r"(c0), "r"(c1), "r"(c2) : "memory");
}
__device__ __forceinline__ void fence_async_global() { asm volatile("fence.proxy.async.global;" ::: "memory"); }
__device__ __forceinline__ void fence_async_smem() { asm volatile("fence.proxy.async.shared::cta;" ::: "memory"); }
__device__ __forceinline__ void tma_2d(uint32_t dst, const CUtensorMap* tm, int c0, int c1, uint32_t bar) {
  asm volatile("cp.async.bulk.tensor.2d.shared::cluster.global.mbarrier::complete_tx::bytes [%0], [%1, {%3, %4}], [%2];"
               ::"r"(dst), "l"(tm), "r"(bar), "r"(c0), "r"(c1) : "memory");
}
__device__ __forceinline__ void tma_3d(uint32_t dst, const CUtensorMap* tm, int c0, int c1, int c2, uint32_t bar) {
  asm volatile("cp.async.bulk.tensor.3d.shared::cluster.global.mbarrier::complete_tx::bytes [%0], [%1, {%3, %4, %5}], [%2];"
               ::"r"(dst), "l"(tm), "r"(bar), "r"(c0), "r"(c1), "r"(c2) : "memory");
}
__device__ __forceinline__ void tma_5d(uint32_t dst, const CUtensorMap* tm, int c0, int c1, int c2, int c3, int c4, uint32_t bar) {
  asm volatile("cp.async.bulk.tensor.5d.shared::cluster.global.mbarrier::complete_tx::bytes [%0], [%1, {%3, %4, %5, %6, %7}], [%2];"
               ::"r"(dst), "l"(tm), "r"(bar), "r"(c0), "r"(c1), "r"(c2), "r"(c3), "r"(c4) : "memory");
}
__device__ __forceinline__ void tma_2d_mc(uint32_t dst, const CUtensorMap* tm, int c0, int c1, uint32_t bar) {
  asm volatile("cp.async.bulk.tensor.2d.shared::cluster.global.mbarrier::complete_tx::bytes.multicast::cluster [%0], [%1, {%3, %4}], [%2], %5;"
               ::"r"(dst), "l"(tm), "r"(bar), "r"(c0), "r"(c1), "h"((uint16_t)3) : "memory");
}
__device__ __forceinline__ void tma_store_2d(const CUtensorMap* tm, uint32_t src, int c0, int c1) {
  asm volatile("cp.async.bulk.tensor.2d.global.shared::cta.bulk_group [%0, {%2, %3}], [%1];"
               ::"l"(tm), "r"(src), "r"(c0), "r"(c1) : "memory");
}
__device__ __forceinline__ bool elect_one() {
  uint32_t p;
  asm volatile("{\n.reg .pred e;\nelect.sync _|e, 0xffffffff;\nselp.u32 %0, 1, 0, e;\n}" : "=r"(p));
  return p != 0;
}
__device__ __forceinline__ void prefetch_tm(const CUtensorMap* tm) {
  asm volatile("prefetch.tensormap [%0];" ::"l"(tm) : "memory");
}
__device__ __forceinline__ void wgmma_fence() { asm volatile("wgmma.fence.sync.aligned;" ::: "memory"); }
__device__ __forceinline__ void wgmma_commit() { asm volatile("wgmma.commit_group.sync.aligned;" ::: "memory"); }
template <int N> __device__ __forceinline__ void wgmma_wait() { asm volatile("wgmma.wait_group.sync.aligned %0;" ::"n"(N) : "memory"); }
__device__ __forceinline__ void wg_bar(int id) {
  if (id == 1) asm volatile("bar.sync 1, 128;" ::: "memory");
  else asm volatile("bar.sync 2, 128;" ::: "memory");
}
template <int R> __device__ __forceinline__ void reg_alloc() { asm volatile("setmaxnreg.inc.sync.aligned.u32 %0;" ::"n"(R)); }
template <int R> __device__ __forceinline__ void reg_dealloc() { asm volatile("setmaxnreg.dec.sync.aligned.u32 %0;" ::"n"(R)); }

__device__ __forceinline__ uint64_t make_desc(uint32_t saddr, uint32_t lbo_bytes, uint32_t sbo_bytes, uint32_t layout) {
  uint64_t d = (uint64_t)((saddr & 0x3FFFF) >> 4);
  d |= (uint64_t)((lbo_bytes & 0x3FFFF) >> 4) << 16;
  d |= (uint64_t)((sbo_bytes & 0x3FFFF) >> 4) << 32;
  d |= (uint64_t)layout << 62;
  return d;
}
__device__ __forceinline__ uint64_t desc128(uint32_t lo) { return ((uint64_t)0x40000040u << 32) | lo; }
__device__ __forceinline__ uint32_t pack_bf16(float lo, float hi) {
  uint32_t r;
  asm("cvt.rn.bf16x2.f32 %0, %1, %2;" : "=r"(r) : "f"(hi), "f"(lo));
  return r;
}
__device__ __forceinline__ float ex2(float x) { float y; asm("ex2.approx.ftz.f32 %0, %1;" : "=f"(y) : "f"(x)); return y; }
__device__ __forceinline__ float rcp(float x) { float y; asm("rcp.approx.ftz.f32 %0, %1;" : "=f"(y) : "f"(x)); return y; }
__device__ __forceinline__ void stmatrix_x4(uint32_t addr, uint32_t r0, uint32_t r1, uint32_t r2, uint32_t r3) {
  asm volatile("stmatrix.sync.aligned.m8n8.x4.shared.b16 [%0], {%1, %2, %3, %4};" ::"r"(addr), "r"(r0), "r"(r1), "r"(r2), "r"(r3) : "memory");
}
template <int N> __device__ __forceinline__ void fence_regs(float (&d)[N]) {
#pragma unroll
  for (int i = 0; i < N; i++) asm volatile("" : "+f"(d[i])::"memory");
}

template <int TA, int TB>
__device__ __forceinline__ void wgmma_m64n128k16_ss(float (&d)[64], uint64_t descA, uint64_t descB) {
  asm volatile("{\n.reg .pred p;\nsetp.ne.b32 p, 1, 0;\n"
    "wgmma.mma_async.sync.aligned.m64n128k16.f32.bf16.bf16 "
    "{%0, %1, %2, %3, %4, %5, %6, %7, %8, %9, %10, %11, %12, %13, %14, %15, %16, %17, %18, %19, %20, %21, %22, %23, %24, %25, %26, %27, %28, %29, %30, %31, %32, %33, %34, %35, %36, %37, %38, %39, %40, %41, %42, %43, %44, %45, %46, %47, %48, %49, %50, %51, %52, %53, %54, %55, %56, %57, %58, %59, %60, %61, %62, %63}, "
    "%64, %65, p, 1, 1, %66, %67;\n}\n"
    : "+f"(d[0]), "+f"(d[1]), "+f"(d[2]), "+f"(d[3]), "+f"(d[4]), "+f"(d[5]), "+f"(d[6]), "+f"(d[7]), "+f"(d[8]), "+f"(d[9]), "+f"(d[10]), "+f"(d[11]), "+f"(d[12]), "+f"(d[13]), "+f"(d[14]), "+f"(d[15]), "+f"(d[16]), "+f"(d[17]), "+f"(d[18]), "+f"(d[19]), "+f"(d[20]), "+f"(d[21]), "+f"(d[22]), "+f"(d[23]), "+f"(d[24]), "+f"(d[25]), "+f"(d[26]), "+f"(d[27]), "+f"(d[28]), "+f"(d[29]), "+f"(d[30]), "+f"(d[31]), "+f"(d[32]), "+f"(d[33]), "+f"(d[34]), "+f"(d[35]), "+f"(d[36]), "+f"(d[37]), "+f"(d[38]), "+f"(d[39]), "+f"(d[40]), "+f"(d[41]), "+f"(d[42]), "+f"(d[43]), "+f"(d[44]), "+f"(d[45]), "+f"(d[46]), "+f"(d[47]), "+f"(d[48]), "+f"(d[49]), "+f"(d[50]), "+f"(d[51]), "+f"(d[52]), "+f"(d[53]), "+f"(d[54]), "+f"(d[55]), "+f"(d[56]), "+f"(d[57]), "+f"(d[58]), "+f"(d[59]), "+f"(d[60]), "+f"(d[61]), "+f"(d[62]), "+f"(d[63])
    : "l"(descA), "l"(descB), "n"(TA), "n"(TB));
}

template <int TA, int TB>
__device__ __forceinline__ void wgmma_m64n32k16_ss(float (&d)[16], uint64_t descA, uint64_t descB) {
  asm volatile("{\n.reg .pred p;\nsetp.ne.b32 p, 1, 0;\n"
    "wgmma.mma_async.sync.aligned.m64n32k16.f32.bf16.bf16 "
    "{%0, %1, %2, %3, %4, %5, %6, %7, %8, %9, %10, %11, %12, %13, %14, %15}, "
    "%16, %17, p, 1, 1, %18, %19;\n}\n"
    : "+f"(d[0]), "+f"(d[1]), "+f"(d[2]), "+f"(d[3]), "+f"(d[4]), "+f"(d[5]), "+f"(d[6]), "+f"(d[7]), "+f"(d[8]), "+f"(d[9]), "+f"(d[10]), "+f"(d[11]), "+f"(d[12]), "+f"(d[13]), "+f"(d[14]), "+f"(d[15])
    : "l"(descA), "l"(descB), "n"(TA), "n"(TB));
}

template <int TA, int TB>
__device__ __forceinline__ void wgmma_m64n32k16_ss_init(float (&d)[16], uint64_t descA, uint64_t descB) {
  asm volatile("{\n.reg .pred p;\nsetp.ne.b32 p, 0, 0;\n"
    "wgmma.mma_async.sync.aligned.m64n32k16.f32.bf16.bf16 "
    "{%0, %1, %2, %3, %4, %5, %6, %7, %8, %9, %10, %11, %12, %13, %14, %15}, "
    "%16, %17, p, 1, 1, %18, %19;\n}\n"
    : "=f"(d[0]), "=f"(d[1]), "=f"(d[2]), "=f"(d[3]), "=f"(d[4]), "=f"(d[5]), "=f"(d[6]), "=f"(d[7]), "=f"(d[8]), "=f"(d[9]), "=f"(d[10]), "=f"(d[11]), "=f"(d[12]), "=f"(d[13]), "=f"(d[14]), "=f"(d[15])
    : "l"(descA), "l"(descB), "n"(TA), "n"(TB));
}

template <int TB>
__device__ __forceinline__ void wgmma_m64n32k16_rs(float (&d)[16], uint32_t a0, uint32_t a1, uint32_t a2, uint32_t a3, uint64_t descB) {
  asm volatile("{\n.reg .pred p;\nsetp.ne.b32 p, 1, 0;\n"
    "wgmma.mma_async.sync.aligned.m64n32k16.f32.bf16.bf16 "
    "{%0, %1, %2, %3, %4, %5, %6, %7, %8, %9, %10, %11, %12, %13, %14, %15}, "
    "{%16, %17, %18, %19}, %20, p, 1, 1, %21;\n}\n"
    : "+f"(d[0]), "+f"(d[1]), "+f"(d[2]), "+f"(d[3]), "+f"(d[4]), "+f"(d[5]), "+f"(d[6]), "+f"(d[7]), "+f"(d[8]), "+f"(d[9]), "+f"(d[10]), "+f"(d[11]), "+f"(d[12]), "+f"(d[13]), "+f"(d[14]), "+f"(d[15])
    : "r"(a0), "r"(a1), "r"(a2), "r"(a3), "l"(descB), "n"(TB));
}

template <int TB>
__device__ __forceinline__ void wgmma_m64n32k16_rs_init(float (&d)[16], uint32_t a0, uint32_t a1, uint32_t a2, uint32_t a3, uint64_t descB) {
  asm volatile("{\n.reg .pred p;\nsetp.ne.b32 p, 0, 0;\n"
    "wgmma.mma_async.sync.aligned.m64n32k16.f32.bf16.bf16 "
    "{%0, %1, %2, %3, %4, %5, %6, %7, %8, %9, %10, %11, %12, %13, %14, %15}, "
    "{%16, %17, %18, %19}, %20, p, 1, 1, %21;\n}\n"
    : "=f"(d[0]), "=f"(d[1]), "=f"(d[2]), "=f"(d[3]), "=f"(d[4]), "=f"(d[5]), "=f"(d[6]), "=f"(d[7]), "=f"(d[8]), "=f"(d[9]), "=f"(d[10]), "=f"(d[11]), "=f"(d[12]), "=f"(d[13]), "=f"(d[14]), "=f"(d[15])
    : "r"(a0), "r"(a1), "r"(a2), "r"(a3), "l"(descB), "n"(TB));
}

template <int TA, int TB>
__device__ __forceinline__ void wgmma_m64n40k16_ss(float (&d)[20], uint64_t descA, uint64_t descB) {
  asm volatile("{\n.reg .pred p;\nsetp.ne.b32 p, 1, 0;\n"
    "wgmma.mma_async.sync.aligned.m64n40k16.f32.bf16.bf16 "
    "{%0, %1, %2, %3, %4, %5, %6, %7, %8, %9, %10, %11, %12, %13, %14, %15, %16, %17, %18, %19}, "
    "%20, %21, p, 1, 1, %22, %23;\n}\n"
    : "+f"(d[0]), "+f"(d[1]), "+f"(d[2]), "+f"(d[3]), "+f"(d[4]), "+f"(d[5]), "+f"(d[6]), "+f"(d[7]), "+f"(d[8]), "+f"(d[9]), "+f"(d[10]), "+f"(d[11]), "+f"(d[12]), "+f"(d[13]), "+f"(d[14]), "+f"(d[15]), "+f"(d[16]), "+f"(d[17]), "+f"(d[18]), "+f"(d[19])
    : "l"(descA), "l"(descB), "n"(TA), "n"(TB));
}

template <int TA, int TB>
__device__ __forceinline__ void wgmma_m64n40k16_ss_init(float (&d)[20], uint64_t descA, uint64_t descB) {
  asm volatile("{\n.reg .pred p;\nsetp.ne.b32 p, 0, 0;\n"
    "wgmma.mma_async.sync.aligned.m64n40k16.f32.bf16.bf16 "
    "{%0, %1, %2, %3, %4, %5, %6, %7, %8, %9, %10, %11, %12, %13, %14, %15, %16, %17, %18, %19}, "
    "%20, %21, p, 1, 1, %22, %23;\n}\n"
    : "=f"(d[0]), "=f"(d[1]), "=f"(d[2]), "=f"(d[3]), "=f"(d[4]), "=f"(d[5]), "=f"(d[6]), "=f"(d[7]), "=f"(d[8]), "=f"(d[9]), "=f"(d[10]), "=f"(d[11]), "=f"(d[12]), "=f"(d[13]), "=f"(d[14]), "=f"(d[15]), "=f"(d[16]), "=f"(d[17]), "=f"(d[18]), "=f"(d[19])
    : "l"(descA), "l"(descB), "n"(TA), "n"(TB));
}

template <int TB>
__device__ __forceinline__ void wgmma_m64n40k16_rs(float (&d)[20], uint32_t a0, uint32_t a1, uint32_t a2, uint32_t a3, uint64_t descB) {
  asm volatile("{\n.reg .pred p;\nsetp.ne.b32 p, 1, 0;\n"
    "wgmma.mma_async.sync.aligned.m64n40k16.f32.bf16.bf16 "
    "{%0, %1, %2, %3, %4, %5, %6, %7, %8, %9, %10, %11, %12, %13, %14, %15, %16, %17, %18, %19}, "
    "{%20, %21, %22, %23}, %24, p, 1, 1, %25;\n}\n"
    : "+f"(d[0]), "+f"(d[1]), "+f"(d[2]), "+f"(d[3]), "+f"(d[4]), "+f"(d[5]), "+f"(d[6]), "+f"(d[7]), "+f"(d[8]), "+f"(d[9]), "+f"(d[10]), "+f"(d[11]), "+f"(d[12]), "+f"(d[13]), "+f"(d[14]), "+f"(d[15]), "+f"(d[16]), "+f"(d[17]), "+f"(d[18]), "+f"(d[19])
    : "r"(a0), "r"(a1), "r"(a2), "r"(a3), "l"(descB), "n"(TB));
}

template <int TB>
__device__ __forceinline__ void wgmma_m64n40k16_rs_init(float (&d)[20], uint32_t a0, uint32_t a1, uint32_t a2, uint32_t a3, uint64_t descB) {
  asm volatile("{\n.reg .pred p;\nsetp.ne.b32 p, 0, 0;\n"
    "wgmma.mma_async.sync.aligned.m64n40k16.f32.bf16.bf16 "
    "{%0, %1, %2, %3, %4, %5, %6, %7, %8, %9, %10, %11, %12, %13, %14, %15, %16, %17, %18, %19}, "
    "{%20, %21, %22, %23}, %24, p, 1, 1, %25;\n}\n"
    : "=f"(d[0]), "=f"(d[1]), "=f"(d[2]), "=f"(d[3]), "=f"(d[4]), "=f"(d[5]), "=f"(d[6]), "=f"(d[7]), "=f"(d[8]), "=f"(d[9]), "=f"(d[10]), "=f"(d[11]), "=f"(d[12]), "=f"(d[13]), "=f"(d[14]), "=f"(d[15]), "=f"(d[16]), "=f"(d[17]), "=f"(d[18]), "=f"(d[19])
    : "r"(a0), "r"(a1), "r"(a2), "r"(a3), "l"(descB), "n"(TB));
}

template <int MODE>
__device__ __forceinline__ void mainloop(float (&acc0)[64], float (&acc1)[64], int it0, int nkb, uint32_t sbase, int cw,
                                         uint32_t ord_parity) {
  const uint32_t bars = sbase + OFF_BAR;
  const int lane = threadIdx.x & 31;
  int stage = it0 % STAGES;
  uint32_t phase = (it0 / STAGES) & 1;
#pragma unroll
  for (int i = 0; i < 64; i++) { acc0[i] = 0.f; acc1[i] = 0.f; }
  mbar_wait(bars + B_ORD + 8 * cw, ord_parity);
  int prev = 0;
  for (int kb = 0; kb < nkb; kb++) {
    mbar_wait(bars + 8 * stage, phase);
    const uint32_t lo = ((sbase & 0x3FFFFu) + stage * STAGE_BYTES) >> 4;
    const uint32_t loK = lo | (1u << 16), loM = lo | (512u << 16);
    wgmma_fence();
#pragma unroll
    for (int k = 0; k < 4; k++) {
      if (MODE == 0) {
        const uint64_t dx = desc128(loK + 1024 + 2 * k);
        wgmma_m64n128k16_ss<0, 0>(acc0, desc128(loK + 2 * k), dx);
        wgmma_m64n128k16_ss<0, 0>(acc1, desc128(loK + 512 + 2 * k), dx);
      } else if (MODE == 1) {
        const uint64_t dw = desc128(loM + 128 * k);
        wgmma_m64n128k16_ss<0, 1>(acc0, desc128(loK + 1024 + 2 * k), dw);
        wgmma_m64n128k16_ss<0, 1>(acc1, desc128(loK + 1536 + 2 * k), dw);
      } else {
        const uint64_t dw = desc128(loK + 2 * k);
        wgmma_m64n128k16_ss<1, 0>(acc0, desc128(loM + 1024 + 128 * k), dw);
        wgmma_m64n128k16_ss<1, 0>(acc1, desc128(loM + 1536 + 128 * k), dw);
      }
      if (k == HANDOFF && kb == nkb - 1 && (threadIdx.x & 127) == 0) mbar_arrive(bars + B_ORD + 8 * (cw ^ 1));
    }
    wgmma_commit();
    wgmma_wait<1>();
    if (kb > 0 && lane < 2) mbar_arrive_cluster(bars + B_EMPTY + 8 * prev, lane);
    prev = stage;
    if (++stage == STAGES) { stage = 0; phase ^= 1; }
  }
  wgmma_wait<0>();
  if (lane < 2) mbar_arrive_cluster(bars + B_EMPTY + 8 * prev, lane);
  fence_regs(acc0);
  fence_regs(acc1);
}

template <int N>
__device__ __forceinline__ void dual_softmax_n(const float (&p)[N][16], uint32_t (&pos)[N][8], uint32_t (&neg)[N][8]) {
  constexpr float L2E = 1.4426950408889634f;
  float ca[N][2], cb[N][2];
  {
    float mx[N][2], mn[N][2];
#pragma unroll
    for (int i = 0; i < N; i++)
#pragma unroll
      for (int r = 0; r < 2; r++) {
        const int o = 2 * r;
        mx[i][r] = fmaxf(fmaxf(fmaxf(p[i][o], p[i][o + 1]), fmaxf(p[i][4 + o], p[i][5 + o])),
                         fmaxf(fmaxf(p[i][8 + o], p[i][9 + o]), fmaxf(p[i][12 + o], p[i][13 + o])));
        mn[i][r] = fminf(fminf(fminf(p[i][o], p[i][o + 1]), fminf(p[i][4 + o], p[i][5 + o])),
                         fminf(fminf(p[i][8 + o], p[i][9 + o]), fminf(p[i][12 + o], p[i][13 + o])));
      }
#pragma unroll
    for (int o = 1; o <= 2; o <<= 1) {
      float tx[N][2], tn[N][2];
#pragma unroll
      for (int i = 0; i < N; i++)
#pragma unroll
        for (int r = 0; r < 2; r++) { tx[i][r] = __shfl_xor_sync(0xffffffffu, mx[i][r], o); tn[i][r] = __shfl_xor_sync(0xffffffffu, mn[i][r], o); }
#pragma unroll
      for (int i = 0; i < N; i++)
#pragma unroll
        for (int r = 0; r < 2; r++) { mx[i][r] = fmaxf(mx[i][r], tx[i][r]); mn[i][r] = fminf(mn[i][r], tn[i][r]); }
    }
#pragma unroll
    for (int i = 0; i < N; i++)
#pragma unroll
      for (int r = 0; r < 2; r++) { ca[i][r] = -mx[i][r] * L2E; cb[i][r] = mn[i][r] * L2E; }
  }
  float ep[2][16], en[2][16];
  float rp[2], rn[2];
#pragma unroll
  for (int i = 0; i <= N; i++) {
    const int cur = i & 1, prv = cur ^ 1;
    if (i > 0) {
      float sp[2], sn[2];
#pragma unroll
      for (int r = 0; r < 2; r++) {
        const int o = 2 * r;
        sp[r] = ((ep[prv][o] + ep[prv][o + 1]) + (ep[prv][4 + o] + ep[prv][5 + o])) + ((ep[prv][8 + o] + ep[prv][9 + o]) + (ep[prv][12 + o] + ep[prv][13 + o]));
        sn[r] = ((en[prv][o] + en[prv][o + 1]) + (en[prv][4 + o] + en[prv][5 + o])) + ((en[prv][8 + o] + en[prv][9 + o]) + (en[prv][12 + o] + en[prv][13 + o]));
      }
      float t0[2], t1[2];
#pragma unroll
      for (int r = 0; r < 2; r++) { t0[r] = __shfl_xor_sync(0xffffffffu, sp[r], 1); t1[r] = __shfl_xor_sync(0xffffffffu, sn[r], 1); }
      if (i < N) {
#pragma unroll
        for (int e = 0; e < 4; e++) {
          ep[cur][e] = ex2(fmaf(p[i][e], L2E, ca[i][e >> 1])); en[cur][e] = ex2(fmaf(p[i][e], -L2E, cb[i][e >> 1]));
        }
      }
#pragma unroll
      for (int r = 0; r < 2; r++) { sp[r] += t0[r]; sn[r] += t1[r]; }
#pragma unroll
      for (int r = 0; r < 2; r++) { t0[r] = __shfl_xor_sync(0xffffffffu, sp[r], 2); t1[r] = __shfl_xor_sync(0xffffffffu, sn[r], 2); }
      if (i < N) {
#pragma unroll
        for (int e = 4; e < 8; e++) {
          ep[cur][e] = ex2(fmaf(p[i][e], L2E, ca[i][(e >> 1) & 1])); en[cur][e] = ex2(fmaf(p[i][e], -L2E, cb[i][(e >> 1) & 1]));
        }
      }
#pragma unroll
      for (int r = 0; r < 2; r++) { rp[r] = rcp(sp[r] + t0[r]); rn[r] = rcp(sn[r] + t1[r]); }
    } else {
#pragma unroll
      for (int e = 0; e < 8; e++) {
        ep[cur][e] = ex2(fmaf(p[i][e], L2E, ca[i][(e >> 1) & 1])); en[cur][e] = ex2(fmaf(p[i][e], -L2E, cb[i][(e >> 1) & 1]));
      }
    }
#pragma unroll
    for (int j = 0; j < 4; j++) {
      if (i < N && j >= 2) {
#pragma unroll
        for (int e = 4 * j; e < 4 * j + 4; e++) {
          ep[cur][e] = ex2(fmaf(p[i][e], L2E, ca[i][(e >> 1) & 1])); en[cur][e] = ex2(fmaf(p[i][e], -L2E, cb[i][(e >> 1) & 1]));
        }
      }
      if (i > 0) {
#pragma unroll
        for (int r = 0; r < 2; r++) {
          pos[i - 1][2 * j + r] = pack_bf16(ep[prv][4 * j + 2 * r] * rp[r], ep[prv][4 * j + 2 * r + 1] * rp[r]);
          neg[i - 1][2 * j + r] = pack_bf16(en[prv][4 * j + 2 * r] * rn[r], en[prv][4 * j + 2 * r + 1] * rn[r]);
        }
      }
    }
  }
}

struct cplx { float r, i; };
__device__ __forceinline__ cplx cmul(cplx a, cplx b) { return {a.r * b.r - a.i * b.i, a.r * b.i + a.i * b.r}; }
__device__ __forceinline__ cplx cfma(cplx a, cplx b, cplx c) {
  return {fmaf(a.r, b.r, fmaf(-a.i, b.i, c.r)), fmaf(a.r, b.i, fmaf(a.i, b.r, c.i))};
}
__device__ __forceinline__ cplx shfl_up_c(cplx v, int d) {
  return {__shfl_up_sync(0xffffffffu, v.r, d, 4), __shfl_up_sync(0xffffffffu, v.i, d, 4)};
}

struct ChanParams { cplx lam, c2; };

__device__ __forceinline__ ChanParams chan_params(float lr, float li, float log_dt) {
  const float dt = __bfloat162float(__float2bfloat16(expf(log_dt)));
  const float mag = expf(dt * lr);
  float sn, cs;
  sincosf(dt * li, &sn, &cs);
  ChanParams c;
  c.lam = {mag * cs, mag * sn};
  const float nr = c.lam.r - 1.0f, ni = c.lam.i;
  const float den = lr * lr + li * li;
  c.c2 = {2.0f * (nr * lr + ni * li) / den, 2.0f * (ni * lr - nr * li) / den};
  return c;
}

__device__ __forceinline__ void epi_bu(float (&are)[64], float (&aim)[64], const ChanParams (&cp)[2],
                                       uint32_t sbase, int G, int chunk, int cw, unsigned epoch) {
  const int lane = threadIdx.x & 31, w = (threadIdx.x & 127) >> 5, q = lane & 3, r8 = lane >> 2;
  cplx E[2] = {{0.f, 0.f}, {0.f, 0.f}};
#pragma unroll
  for (int k8 = 0; k8 < 16; k8++)
#pragma unroll
    for (int e = 0; e < 2; e++)
#pragma unroll
      for (int c = 0; c < 2; c++) E[c] = cfma(cp[c].lam, E[c], cplx{are[4 * k8 + 2 * c + e], aim[4 * k8 + 2 * c + e]});
  cplx L32[2], L128[2], prev[2];
#pragma unroll
  for (int c = 0; c < 2; c++) {
    cplx l = cp[c].lam;
#pragma unroll
    for (int s = 0; s < 5; s++) l = cmul(l, l);
    L32[c] = l;
    const cplx l64 = cmul(l, l);
    L128[c] = cmul(l64, l64);
    cplx t = shfl_up_c(E[c], 1);
    if (q >= 1) E[c] = cfma(L32[c], t, E[c]);
    t = shfl_up_c(E[c], 2);
    if (q >= 2) E[c] = cfma(l64, t, E[c]);
    prev[c] = shfl_up_c(E[c], 1);
    if (q == 0) prev[c] = {0.f, 0.f};
  }
  uint4* gE = g_E + (size_t)G * 16 * 64 + 16 * w + r8;
  if (q == 3) {
    st_tagged(gE + chunk * 64, E[0].r, E[0].i, epoch);
    st_tagged(gE + chunk * 64 + 8, E[1].r, E[1].i, epoch);
  }
  cplx V[2][4];
  {
    unsigned long long w0[8], w1[8];
    unsigned pending = 0;
#pragma unroll
    for (int i = 0; i < 8; i++) {
      w0[i] = 0ull; w1[i] = 0ull;
      if (chunk - 1 - 4 * q - (i & 3) >= 0) pending |= 1u << i;
    }
    unsigned spins = 0;
    if (chunk > 0) __nanosleep(600);
    while (true) {
#pragma unroll
      for (int i = 0; i < 8; i++)
        asm volatile("{\n.reg .pred p;\nsetp.ne.u32 p, %3, 0;\n@p ld.relaxed.gpu.global.v2.b64 {%0, %1}, [%2];\n}"
                     : "+l"(w0[i]), "+l"(w1[i]) : "l"(gE + (chunk - 1 - 4 * q - (i & 3)) * 64 + 8 * (i >> 2)), "r"(pending & (1u << i)) : "memory");
#pragma unroll
      for (int i = 0; i < 8; i++)
        if ((unsigned)(w0[i] >> 32) == epoch && (unsigned)(w1[i] >> 32) == epoch) pending &= ~(1u << i);
      if (__all_sync(0xffffffffu, pending == 0)) break;
      __nanosleep(300);
      if (give_up(sbase + OFF_BAR, ++spins)) break;
    }
#pragma unroll
    for (int i = 0; i < 8; i++) V[i >> 2][i & 3] = {__uint_as_float((unsigned)w0[i]), __uint_as_float((unsigned)w1[i])};
  }
  cplx s[2];
#pragma unroll
  for (int c = 0; c < 2; c++) {
    cplx Pq = V[c][3];
#pragma unroll
    for (int jj = 2; jj >= 0; jj--) Pq = cfma(L128[c], Pq, V[c][jj]);
    const cplx l256 = cmul(L128[c], L128[c]);
    const cplx l512 = cmul(l256, l256);
    cplx F = {1.f, 0.f};
    cplx G32 = {1.f, 0.f};
    if (q >= 1) { F = l512; G32 = L32[c]; }
    if (q >= 2) { F = cmul(F, l512); G32 = cmul(G32, L32[c]); }
    if (q >= 3) { F = cmul(F, l512); G32 = cmul(G32, L32[c]); }
    Pq = cmul(Pq, F);
#pragma unroll
    for (int o = 1; o <= 2; o <<= 1) {
      Pq.r += __shfl_xor_sync(0xffffffffu, Pq.r, o);
      Pq.i += __shfl_xor_sync(0xffffffffu, Pq.i, o);
    }
    s[c] = cfma(G32, Pq, prev[c]);
  }
  if (cw == 1) mbar_wait(sbase + OFF_BAR + B_EBF, 0);
#pragma unroll
  for (int qq = 0; qq < 4; qq++) {
    uint32_t ore[2][4], oim[2][4];
#pragma unroll
    for (int kk = 0; kk < 4; kk++) {
      const int k8 = 4 * qq + kk;
      float hr[2][2], hi[2][2];
#pragma unroll
      for (int e = 0; e < 2; e++)
#pragma unroll
        for (int c = 0; c < 2; c++) {
          s[c] = cfma(cp[c].lam, s[c], cplx{are[4 * k8 + 2 * c + e], aim[4 * k8 + 2 * c + e]});
          hr[c][e] = fmaf(cp[c].c2.r, s[c].r, -cp[c].c2.i * s[c].i);
          hi[c][e] = -fmaf(cp[c].c2.r, s[c].i, cp[c].c2.i * s[c].r);
        }
#pragma unroll
      for (int c = 0; c < 2; c++) {
        ore[c][kk] = pack_bf16(hr[c][0], hr[c][1]);
        oim[c][kk] = pack_bf16(hi[c][0], hi[c][1]);
      }
    }
#pragma unroll
    for (int c = 0; c < 2; c++) {
      const int row = 16 * w + r8 + 8 * c;
      const uint32_t addr = sbase + OFF_PHI + (qq >> 1) * 8192 + row * 128 + ((((qq & 1) * 4 + q) ^ (row & 7)) << 4);
      asm volatile("st.shared.v4.b32 [%0], {%1, %2, %3, %4};" ::"r"(addr), "r"(ore[c][0]), "r"(ore[c][1]), "r"(ore[c][2]), "r"(ore[c][3]) : "memory");
      asm volatile("st.shared.v4.b32 [%0], {%1, %2, %3, %4};" ::"r"(addr + 32768), "r"(oim[c][0]), "r"(oim[c][1]), "r"(oim[c][2]), "r"(oim[c][3]) : "memory");
    }
  }
  fence_async_smem();
  wg_bar(1 + cw);
  if ((threadIdx.x & 127) == 0) mbar_arrive(sbase + OFF_BAR + B_JOB + 8 * cw);
}

__device__ __forceinline__ void q_issue_num(float (&num)[20], const uint32_t (&pos)[8], const uint32_t (&neg)[8], uint32_t b) {
  wgmma_fence();
  wgmma_m64n40k16_rs_init<1>(num, pos[0], pos[1], pos[2], pos[3], make_desc(b, 640, 128, 0));
  wgmma_m64n40k16_rs<1>(num, pos[4], pos[5], pos[6], pos[7], make_desc(b + 1280, 640, 128, 0));
  wgmma_m64n40k16_rs<1>(num, neg[0], neg[1], neg[2], neg[3], make_desc(b + 2560, 640, 128, 0));
  wgmma_m64n40k16_rs<1>(num, neg[4], neg[5], neg[6], neg[7], make_desc(b + 3840, 640, 128, 0));
  wgmma_commit();
}
__device__ __forceinline__ void q_store_o(const float (&num)[20], uint32_t rowaddr, int chunk0) {
  const int lane = threadIdx.x & 31, mi = lane >> 3, rin = lane & 7;
  const float d0 = __shfl_sync(0xffffffffu, num[16], lane & ~3), d1 = __shfl_sync(0xffffffffu, num[18], lane & ~3);
  const float i0 = __fdividef(1.0f, d0 + 1e-6f), i1 = __fdividef(1.0f, d1 + 1e-6f);
#pragma unroll
  for (int jp = 0; jp < 2; jp++) {
    const int c0 = chunk0 + jp * 2 + (mi >> 1);
    stmatrix_x4(rowaddr + ((c0 ^ rin) << 4), pack_bf16(num[8 * jp] * i0, num[8 * jp + 1] * i0),
                pack_bf16(num[8 * jp + 2] * i1, num[8 * jp + 3] * i1), pack_bf16(num[8 * jp + 4] * i0, num[8 * jp + 5] * i0),
                pack_bf16(num[8 * jp + 6] * i1, num[8 * jp + 7] * i1));
  }
}
__device__ __forceinline__ void epi_attn(float (&acc0)[64], float (&acc1)[64], uint32_t sbase, int cw, bool isq) {
  const int t = threadIdx.x & 127, lane = t & 31, w = t >> 5, q = lane & 3, r8 = lane >> 2;
  const int mi = lane >> 3, rin = lane & 7;
  const int row0 = w * 16 + (mi & 1) * 8 + rin;
  uint32_t kf[2][16];
  if (isq) {
#pragma unroll
    for (int j = 0; j < 16; j += 2) {
      const uint32_t addr = sbase + OFF_PHI + (j >> 3) * 16384 + row0 * 128 + ((((j & 7) + (mi >> 1)) ^ rin) << 4);
      stmatrix_x4(addr, pack_bf16(acc0[4 * j], acc0[4 * j + 1]), pack_bf16(acc0[4 * j + 2], acc0[4 * j + 3]),
                  pack_bf16(acc0[4 * j + 4], acc0[4 * j + 5]), pack_bf16(acc0[4 * j + 6], acc0[4 * j + 7]));
      stmatrix_x4(addr + 8192, pack_bf16(acc1[4 * j], acc1[4 * j + 1]), pack_bf16(acc1[4 * j + 2], acc1[4 * j + 3]),
                  pack_bf16(acc1[4 * j + 4], acc1[4 * j + 5]), pack_bf16(acc1[4 * j + 6], acc1[4 * j + 7]));
    }
#pragma unroll
    for (int i = 0; i < 16; i++) { kf[0][i] = 0; kf[1][i] = 0; }
  } else {
#pragma unroll
    for (int j = 8; j < 16; j += 2) {
      const uint32_t addr = sbase + OFF_PHI + 16384 + ((j - 8) >> 2) * 8192 + row0 * 64 + ((((j & 3) + (mi >> 1)) ^ ((row0 >> 1) & 3)) << 4);
      stmatrix_x4(addr, pack_bf16(acc0[4 * j], acc0[4 * j + 1]), pack_bf16(acc0[4 * j + 2], acc0[4 * j + 3]),
                  pack_bf16(acc0[4 * j + 4], acc0[4 * j + 5]), pack_bf16(acc0[4 * j + 6], acc0[4 * j + 7]));
      stmatrix_x4(addr + 4096, pack_bf16(acc1[4 * j], acc1[4 * j + 1]), pack_bf16(acc1[4 * j + 2], acc1[4 * j + 3]),
                  pack_bf16(acc1[4 * j + 4], acc1[4 * j + 5]), pack_bf16(acc1[4 * j + 6], acc1[4 * j + 7]));
    }
#pragma unroll
    for (int i = 0; i < 16; i++) {
      kf[0][i] = pack_bf16(acc0[2 * i], acc0[2 * i + 1]);
      kf[1][i] = pack_bf16(acc1[2 * i], acc1[2 * i + 1]);
    }
  }
  fence_async_smem();
  wg_bar(1 + cw);
  const int nsub = isq ? 2 : 1;
#pragma unroll 1
  for (int sub = 0; sub < nsub; sub++) {
    const int it = 4 * sub;
    (void)it;
    const uint32_t tile = sbase + OFF_PHI + sub * 16384;
    const uint32_t wp = sbase + OFF_WPHI + (isq ? 2 * sub : 2 * cw) * 2048;
    float pq[4][16];
    uint32_t pos[4][8], neg[4][8];
    if (isq) {
      wgmma_fence();
#pragma unroll
      for (int i = 0; i < 4; i++) {
        const uint32_t a = tile + (i & 1) * 8192 + (i >> 1) * 64, b = wp + (i >> 1) * 2048;
        wgmma_m64n32k16_ss_init<0, 1>(pq[i], make_desc(a, 16, 1024, 1), make_desc(b, 512, 512, 2));
        wgmma_m64n32k16_ss<0, 1>(pq[i], make_desc(a + 32, 16, 1024, 1), make_desc(b + 1024, 512, 512, 2));
      }
    } else {
      wgmma_fence();
#pragma unroll
      for (int i = 0; i < 4; i++) {
        const uint32_t b = wp + (i >> 1) * 2048;
        const uint32_t* f = &kf[i & 1][8 * (i >> 1)];
        wgmma_m64n32k16_rs_init<1>(pq[i], f[0], f[1], f[2], f[3], make_desc(b, 512, 512, 2));
        wgmma_m64n32k16_rs<1>(pq[i], f[4], f[5], f[6], f[7], make_desc(b + 1024, 512, 512, 2));
      }
    }
    wgmma_commit();
    wgmma_wait<0>();
#pragma unroll
    for (int i = 0; i < 4; i++) fence_regs(pq[i]);
    dual_softmax_n<4>(pq, pos, neg);
    if (!isq) {
      float kvacc[2][20];
      mbar_wait(sbase + OFF_BAR + B_EBF + 8 + 8 * cw, 0);
#pragma unroll
      for (int hh = 0; hh < 2; hh++) {
#pragma unroll
        for (int half = 0; half < 2; half++) {
          const uint32_t rb = sbase + OFF_PHI + hh * 32768 + (half * 64 + row0) * 128;
#pragma unroll
          for (int jp = 0; jp < 2; jp++) {
            const int c0 = jp * 2 + (mi >> 1), i = 2 * hh + half;
            stmatrix_x4(rb + ((c0 ^ rin) << 4), pos[i][4 * jp], pos[i][4 * jp + 1], pos[i][4 * jp + 2], pos[i][4 * jp + 3]);
            stmatrix_x4(rb + (((c0 + 4) ^ rin) << 4), neg[i][4 * jp], neg[i][4 * jp + 1], neg[i][4 * jp + 2], neg[i][4 * jp + 3]);
          }
        }
      }
      fence_async_smem();
      wg_bar(1 + cw);
      wgmma_fence();
#pragma unroll
      for (int hh = 0; hh < 2; hh++)
#pragma unroll
        for (int ks = 0; ks < 8; ks++) {
          const uint32_t vb = sbase + OFF_PHI + 16384 + hh * 8192 + ks * 1024;
          const uint64_t da = make_desc(sbase + OFF_PHI + hh * 32768 + ks * 2048, 1024, 1024, 1);
          const uint64_t db = make_desc(vb, sbase + OFF_ONES - vb, 512, 2);
          if (ks == 0) wgmma_m64n40k16_ss_init<1, 1>(kvacc[hh], da, db);
          else wgmma_m64n40k16_ss<1, 1>(kvacc[hh], da, db);
        }
      wgmma_commit();
      wgmma_wait<0>();
      fence_regs(kvacc[0]);
      fence_regs(kvacc[1]);
      wg_bar(1 + cw);
      if (t == 0) mbar_arrive(sbase + OFF_BAR + B_EBA + 8 * cw);
#pragma unroll
      for (int hh = 0; hh < 2; hh++) {
#pragma unroll
        for (int rr = 0; rr < 2; rr++) {
          const int off = ((16 * w + r8 + 8 * rr) * KVW + 2 * q) * 4;
#pragma unroll
          for (int j = 0; j < 5; j++) {
            const int o = off + 32 * j;
            const uint32_t dst = (hh == 0) ? sbase + OFF_PHI + o
                                           : (o < 6144 ? sbase + OFF_PHI + 10240 + o : sbase + OFF_V + 16384 - 6144 + o);
            asm volatile("st.shared.v2.f32 [%0], {%1, %2};" ::"r"(dst), "f"(kvacc[hh][4 * j + 2 * rr]), "f"(kvacc[hh][4 * j + 2 * rr + 1]) : "memory");
          }
        }
      }
      fence_async_smem();
      wg_bar(1 + cw);
      if (t == 0) mbar_arrive(sbase + OFF_BAR + B_JOB + 16 + 8 * cw);
    } else {
      float num[4][20];
      mbar_wait(sbase + OFF_BAR + B_KVX + 8 * sub, 0);
#pragma unroll
      for (int i = 0; i < 4; i++) q_issue_num(num[i], pos[i], neg[i], sbase + OFF_V + (2 * sub + (i >> 1)) * 5120);
      wgmma_wait<2>();
      fence_regs(num[0]); fence_regs(num[1]);
      q_store_o(num[0], tile + row0 * 128, 0);
      q_store_o(num[1], tile + 8192 + row0 * 128, 0);
      wgmma_wait<0>();
      fence_regs(num[2]); fence_regs(num[3]);
      q_store_o(num[2], tile + row0 * 128, 4);
      q_store_o(num[3], tile + 8192 + row0 * 128, 4);
      fence_async_smem();
      wg_bar(1);
      if (t == 0) mbar_arrive(sbase + OFF_BAR + B_JOB + 32 + 8 * sub);
    }
  }
}

__device__ __forceinline__ void helper_kv(uint32_t sbase, int g, unsigned epoch) {
  const int h = threadIdx.x - 64;
  mbar_wait_long(sbase + OFF_BAR + B_EBA + 8, 0);
#pragma unroll 1
  for (int pr = 0; pr < 2; pr++) {
    if ((h & 31) == 0) {
      wait_ge(sbase + OFF_BAR, &g_flags.kvcnt[(g + 8 * pr) * 8], 16u * epoch);
    }
    __syncwarp();
    const float4* src = reinterpret_cast<const float4*>(g_kv + (size_t)(2 * g + 16 * pr) * 64 * KVW);
#pragma unroll 1
    for (int ib = 0; ib < 3; ib++) {
      float4 u[7];
#pragma unroll
      for (int i = 0; i < 7; i++) u[i] = __ldcg(src + min((ib * 7 + i) * 64 + h, 1279));
#pragma unroll
      for (int i = 0; i < 7; i++) {
        const int idx = min((ib * 7 + i) * 64 + h, 1279);
        const int f2 = idx / 10, j = idx - f2 * 10;
        const uint32_t dst = sbase + OFF_V + pr * 10240 + (f2 >> 3) * 640 + (j >> 1) * 128 + (f2 & 7) * 16 + (j & 1) * 8;
        asm volatile("st.shared.v2.b32 [%0], {%1, %2};" ::"r"(dst), "r"(pack_bf16(u[i].x, u[i].y)), "r"(pack_bf16(u[i].z, u[i].w)) : "memory");
      }
    }
    fence_async_smem();
    __syncwarp();
    if ((h & 31) == 0) mbar_arrive(sbase + OFF_BAR + B_KVX + 8 * pr);
  }
}

__device__ __forceinline__ void store_agent(const Params& prm, uint32_t sbase, int g, int rb, unsigned epoch) {
  const uint32_t bars = sbase + OFF_BAR;
#pragma unroll 1
  for (int j = 0; j < 6; j++) {
    mbar_wait_long(bars + B_JOB + 8 * j, 0);
    unsigned* flag;
    if (j < 2) {
      const int G = g + 8 * j;
#pragma unroll 1
      for (int u = 0; u < 16; u++) {
        tma_store_3d(&prm.tmHTs, sbase + OFF_PHI + (u & 7) * 2048 + (u >> 3) * 32768, 0, (u >> 3) * 1024 + 64 * G + (u & 3) * 16, 2 * rb + ((u >> 2) & 1));
        __nanosleep(PACE_HT);
      }
      flag = &g_flags.hcnt[rb * 8];
    } else if (j < 4) {
      const int hp = g + 8 * (j - 2);
      wait_ge(bars, &g_flags.zero_cnt, 128u * epoch);
      fence_async_global();
#pragma unroll 1
      for (int u = 0; u < 10; u++) {
        const uint32_t o = u * 2048;
        const uint32_t src = (o < 16384) ? sbase + OFF_PHI + o : sbase + OFF_V + o;
        bulk_reduce_f32(g_kv + (size_t)(2 * hp) * 64 * KVW + o / 4, src, 2048);
        if (j == 2 || PACE_KV3) __nanosleep(PACE_KV);
      }
      flag = &g_flags.kvcnt[hp * 8];
    } else {
      tma_store_2d(&prm.tmO, sbase + OFF_PHI + (j - 4) * 16384, 64 * (g + 8 * (j - 4)), 128 * rb);
      flag = &g_flags.ocnt[(2 * rb + (j - 4)) * 8];
    }
    bulk_commit();
    if (j != 4) {
      bulk_wait_read();
      mbar_arrive(bars + B_EBF + 8 * (j < 4 ? j : 4));
    }
    bulk_wait_all();
    red_relaxed_add(flag, 1);
  }
}

constexpr int OST = 544;
__device__ __forceinline__ void stage_half(const float (&a)[64], uint32_t wbuf) {
  const int lane = threadIdx.x & 31, q = lane & 3, r8 = lane >> 2;
#pragma unroll
  for (int j = 0; j < 16; j++) {
    asm volatile("st.shared.v2.f32 [%0], {%1, %2};" ::"r"(wbuf + r8 * OST + j * 32 + q * 8), "f"(a[4 * j]), "f"(a[4 * j + 1]) : "memory");
    asm volatile("st.shared.v2.f32 [%0], {%1, %2};" ::"r"(wbuf + (r8 + 8) * OST + j * 32 + q * 8), "f"(a[4 * j + 2]), "f"(a[4 * j + 3]) : "memory");
  }
  __syncwarp();
}
__device__ __forceinline__ float4 lds128(uint32_t addr) {
  float4 v;
  asm volatile("ld.shared.v4.f32 {%0, %1, %2, %3}, [%4];" : "=f"(v.x), "=f"(v.y), "=f"(v.z), "=f"(v.w) : "r"(addr) : "memory");
  return v;
}
__device__ __forceinline__ void store_y(float (&acc0)[64], const float (&acc1)[64], uint32_t wbuf, const Params& prm, int rb, int g) {
  const int lane = threadIdx.x & 31, w = (threadIdx.x & 127) >> 5;
  const uint2 dk = __ldg(reinterpret_cast<const uint2*>(prm.dskip + 128 * g) + lane);
#pragma unroll 1
  for (int half = 0; half < 2; half++) {
    const int m0 = 64 * half + 16 * w;
    const int t0 = rb * 128 + 32 * ((m0 >> 3) & 3) + 8 * (m0 >> 5);
    uint2 xs[16];
#pragma unroll
    for (int r = 0; r < 16; r++)
      xs[r] = __ldg(reinterpret_cast<const uint2*>(prm.xB + (size_t)(t0 + (r & 7) + (r >> 3) * 32) * DM + 128 * g) + lane);
    stage_half(acc0, wbuf);
    float* dst = prm.out + (size_t)t0 * 2048 + 1024 + 128 * g + 4 * lane;
#pragma unroll
    for (int r = 0; r < 16; r++) {
      float4 v = lds128(wbuf + r * OST + lane * 16);
      const float2 s0 = __bfloat1622float2(__hmul2(*reinterpret_cast<const __nv_bfloat162*>(&xs[r].x), *reinterpret_cast<const __nv_bfloat162*>(&dk.x)));
      const float2 s1 = __bfloat1622float2(__hmul2(*reinterpret_cast<const __nv_bfloat162*>(&xs[r].y), *reinterpret_cast<const __nv_bfloat162*>(&dk.y)));
      v.x += s0.x; v.y += s0.y; v.z += s1.x; v.w += s1.y;
      STOUT(reinterpret_cast<float4*>(dst + (size_t)((r & 7) + (r >> 3) * 32) * 2048), v);
    }
    __syncwarp();
#pragma unroll
    for (int i = 0; i < 64; i++) acc0[i] = acc1[i];
  }
}
__device__ __forceinline__ void drain_out(uint32_t wbuf, float* dst  ) {
  const int lane = threadIdx.x & 31;
#pragma unroll
  for (int r = 0; r < 16; r++) {
    const float4 v = lds128(wbuf + r * OST + lane * 16);
    const uint32_t p0 = pack_bf16(v.x, v.y), p1 = pack_bf16(v.z, v.w);
    STOUT(reinterpret_cast<float4*>(dst + (size_t)r * 2048) + lane,
           make_float4(__uint_as_float(p0 << 16), __uint_as_float(p0 & 0xffff0000u), __uint_as_float(p1 << 16), __uint_as_float(p1 & 0xffff0000u)));
  }
}

__global__ void __launch_bounds__(384, 1) fused_kernel(const __grid_constant__ Params prm) {
  extern __shared__ uint8_t smem_raw[];
  const uint32_t sbase = (smem_u32(smem_raw) + 1023) & ~1023u;
  const uint32_t bars = sbase + OFF_BAR;
  const int tid = threadIdx.x, wg = __shfl_sync(0xffffffffu, tid >> 7, 0);
  const int cl = blockIdx.x >> 1, rank = blockIdx.x & 1;
  const int g = cl >> 3, rb = 2 * (cl & 7) + rank;

  if (tid == 0) {
    for (int s = 0; s < STAGES; s++) { mbar_init(bars + 8 * s, 1);
      mbar_init(bars + B_EMPTY + 8 * s, 8);
    }
    mbar_init(bars + B_ORD, 1); mbar_init(bars + B_ORD + 8, 1); mbar_init(bars + B_WPHI, 1); mbar_init(bars + B_EPOCH, 1); mbar_init(bars + B_KVX, 2); mbar_init(bars + B_KVX + 8, 2);
    for (int j = 0; j < 6; j++) mbar_init(bars + B_JOB + 8 * j, 1);
    mbar_init(bars + B_PARAM, 2); mbar_init(bars + B_EBA, 1); mbar_init(bars + B_EBA + 8, 1);
    for (int j = 0; j < 5; j++) mbar_init(bars + B_EBF + 8 * j, 1);
    asm volatile("st.shared.u32 [%0], %1;" ::"r"(bars + B_DEAD), "r"(0u) : "memory");
    asm volatile("fence.mbarrier_init.release.cluster;" ::: "memory");
    asm volatile("fence.proxy.async.shared::cta;" ::: "memory");
#pragma unroll 1
    for (int kb = 0; kb < STAGES; kb++) {
      const uint32_t full = bars + 8 * kb, sw = sbase + kb * STAGE_BYTES;
      mbar_expect_tx(full, STAGE_BYTES);
      tma_5d(sw + 16384, &prm.tmXB, kb * 64, 0, 0, 0, rb, full);
      tma_2d(sw, &prm.tmBre, kb * 64, 64 * g, full);
      tma_2d(sw + 8192, &prm.tmBim, kb * 64, 64 * g, full);
    }
  } else if (tid == 32) {
    prefetch_tm(&prm.tmXB); prefetch_tm(rank ? &prm.tmBim : &prm.tmBre); prefetch_tm(&prm.tmWphi);
    prefetch_tm(&prm.tmXA); prefetch_tm(&prm.tmWqkv); prefetch_tm(&prm.tmHT);
    prefetch_tm(&prm.tmCre); prefetch_tm(&prm.tmCim); prefetch_tm(&prm.tmO); prefetch_tm(&prm.tmWo);
  } else if (tid >= 64 && tid < 128) {
    asm volatile("st.shared.v4.b32 [%0], {%1, %2, %2, %2};" ::"r"(sbase + OFF_ONES + (tid - 64) * 16), "r"(0x00003F80u), "r"(0u) : "memory");
    fence_async_smem();
  }
  __syncthreads();
  asm volatile("barrier.cluster.arrive.relaxed.aligned;\nbarrier.cluster.wait.acquire.aligned;" ::: "memory");

  if (wg == 0) {
    reg_dealloc<56>();
    const int warp = __shfl_sync(0xffffffffu, tid >> 5, 0), lane = tid & 31;
    if (warp == 0) {
      const bool leader = elect_one();
      if (leader) {
        mbar_expect_tx(bars + B_WPHI, 8192);
        tma_2d(sbase + OFF_WPHI, &prm.tmWphi, 0, 64 * g, bars + B_WPHI);
        tma_2d(sbase + OFF_WPHI + 4096, &prm.tmWphi, 0, 64 * g + 512, bars + B_WPHI);
      }
      int stage = 0;
      uint32_t phase = 0;
      unsigned epoch = 0;
      auto run = [&](auto kind, const CUtensorMap* tw, int w0, const CUtensorMap* tx, int kb0, int kb1) {
        constexpr int KIND = decltype(kind)::value;
#pragma unroll 1
        for (int kb = kb0; kb < kb1; kb++) {
          mbar_wait(bars + B_EMPTY + 8 * stage, phase);

          if (leader) {
            const uint32_t full = bars + 8 * stage;
            const uint32_t sw = sbase + stage * STAGE_BYTES;
            mbar_expect_tx(full, STAGE_BYTES);
            if (KIND == 0) {
              tma_2d_mc(sw + rank * 8192, tw, kb * 64, w0, full);
              tma_5d(sw + 16384, tx, kb * 64, 0, 0, 0, rb, full);
            } else if (KIND == 1) {
              tma_2d_mc(sw + rank * 8192, tw, w0, kb * 64, full);
              tma_2d(sw + 16384, tx, kb * 64, rb * 128, full);
            } else {
              tma_2d_mc(sw + rank * 8192, tw, (kb & 15) * 64, w0, full);
              tma_3d(sw + 16384, tx, 0, kb * 64, 2 * rb, full);
            }
          }
          if (++stage == STAGES) { stage = 0; phase ^= 1; }
        }
      };
      using K0 = std::integral_constant<int, 0>;
      using K1 = std::integral_constant<int, 1>;
      using K2 = std::integral_constant<int, 2>;
#pragma unroll 1
      for (int i = 0; i < 2; i++) run(K0{}, rank ? &prm.tmBim : &prm.tmBre, 64 * (g + 8 * i), &prm.tmXB, i == 0 ? STAGES : 0, 16);
#pragma unroll 1
      for (int i = 0; i < 3; i++)
        run(K1{}, &prm.tmWqkv, i < 2 ? 1024 + rank * 1024 + 64 * (g + 8 * i) : 64 * (g + 8 * rank), &prm.tmXA, 0, 16);
      mbar_wait(bars + B_EPOCH, 0);
      asm volatile("ld.shared.u32 %0, [%1];" : "=r"(epoch) : "r"(bars + B_EPOCHV) : "memory");
      wait_ge(bars, &g_flags.hcnt[rb * 8], 16u * epoch);
      fence_async_global();
#pragma unroll 1
      for (int i = 0; i < 2; i++) run(K2{}, i ? &prm.tmCim : &prm.tmCre, 128 * g + 64 * rank, &prm.tmHT, 16 * i, 16 * i + 16);
#pragma unroll 1
      for (int i = 0; i < 2; i++) {
        wait_ge(bars, &g_flags.ocnt[(2 * rb + i) * 8], 8u * epoch);
        fence_async_global();
        run(K1{}, &prm.tmWo, 128 * g + 64 * rank, &prm.tmO, 8 * i, 8 * i + 8);
      }
    } else if (warp == 1) {
      unsigned epoch = 0;
      if (lane == 0) {
        epoch = (atomicAdd(&g_flags.ticket, 1u) >> 7) + 1u;
        asm volatile("st.shared.u32 [%0], %1;" ::"r"(bars + B_EPOCHV), "r"(epoch) : "memory");
        mbar_arrive(bars + B_EPOCH);
      }
      uint4* z = reinterpret_cast<uint4*>(g_kv) + blockIdx.x * 160;
#pragma unroll
      for (int i = 0; i < 5; i++) __stcg(z + i * 32 + lane, make_uint4(0, 0, 0, 0));
      __syncwarp();
      if (lane == 0) {
        red_release_add(&g_flags.zero_cnt, 1);
        store_agent(prm, sbase, g, rb, epoch);
      }
    } else {
#pragma unroll 1
      for (int c = 0; c < 2; c++) {
        const int ch = tid - 64, p = 64 * (g + 8 * c) + ch;
        const ChanParams cp = chan_params(__bfloat162float(prm.lam_re[p]), __bfloat162float(prm.lam_im[p]), __bfloat162float(prm.log_dt[p]));
        asm volatile("st.shared.v4.f32 [%0], {%1, %2, %3, %4};" ::"r"(sbase + OFF_V + 16384 + (c * 64 + ch) * 16), "f"(cp.lam.r), "f"(cp.lam.i),
                     "f"(cp.c2.r), "f"(cp.c2.i) : "memory");
      }
      __syncwarp();
      if (lane == 0) mbar_arrive(bars + B_PARAM);
      unsigned epoch;
      mbar_wait(bars + B_EPOCH, 0);
      asm volatile("ld.shared.u32 %0, [%1];" : "=r"(epoch) : "r"(bars + B_EPOCHV) : "memory");
      helper_kv(sbase, g, epoch);
    }
    __syncwarp();
    asm volatile("barrier.cluster.arrive.relaxed.aligned;\nbarrier.cluster.wait.aligned;" ::: "memory");
  } else {
    reg_alloc<224>();
    const int cw = wg - 1;
    const int t = tid & 127, lane = t & 31, w = t >> 5, r8 = lane >> 2;
    float acc0[64], acc1[64];
    unsigned epoch;
    {
      const int G = g + 8 * cw;
      ChanParams cp[2];
      mainloop<0>(acc0, acc1, 16 * cw, 16, sbase, cw, cw ^ 1);
      mbar_wait(bars + B_PARAM, 0);
#pragma unroll
      for (int c = 0; c < 2; c++) {
        const float4 v = lds128(sbase + OFF_V + 16384 + (cw * 64 + 16 * w + r8 + 8 * c) * 16);
        cp[c].lam = {v.x, v.y};
        cp[c].c2 = {v.z, v.w};
      }
      mbar_wait(bars + B_EPOCH, 0);
      asm volatile("ld.shared.u32 %0, [%1];" : "=r"(epoch) : "r"(bars + B_EPOCHV) : "memory");
      epi_bu(acc0, acc1, cp, sbase, G, rb, cw, epoch);
    }
#pragma unroll 1
    for (int step = 0; step < 3; step++) {
      const int it0 = cw ? 48 : (step == 0 ? 32 : (step == 1 ? 64 : 112));
      mainloop<1>(acc0, acc1, it0, 16, sbase, cw, cw ? 1 : (step & 1));
      if (step == 2) {
        stage_half(acc1, sbase + (4 + w) * 16 * OST);
        asm volatile("bar.arrive 3, 256;" ::: "memory");
        stage_half(acc0, sbase + w * 16 * OST);
        drain_out(sbase + w * 16 * OST, prm.out + (size_t)(rb * 128 + 16 * w) * 2048 + 128 * g);
        break;
      }
      mbar_wait(bars + B_WPHI, 0);
      if (cw == 1) {
        mbar_wait(bars + B_EBA, 0);
      } else if (step == 1) {
        mbar_wait(bars + B_EBA + 8, 0);
        mbar_wait(bars + B_EBF + 24, 0);
      }
      epi_attn(acc0, acc1, sbase, cw, step == 1);
      if (cw == 1) break;
    }
    if (cw == 1) {
      mainloop<2>(acc0, acc1, 80, 32, sbase, 1, 0);
      mbar_wait(bars + B_EBF + 32, 0);
      store_y(acc0, acc1, sbase + OFF_EB + w * 16 * OST, prm, rb, g);
      asm volatile("bar.sync 3, 256;" ::: "memory");
      drain_out(sbase + (4 + w) * 16 * OST, prm.out + (size_t)(rb * 128 + 64 + 16 * w) * 2048 + 128 * g);
    }
    asm volatile("barrier.cluster.arrive.relaxed.aligned;\nbarrier.cluster.wait.aligned;" ::: "memory");
  }
}

typedef CUresult (*PFN_encodeTiled)(CUtensorMap*, CUtensorMapDataType, cuuint32_t, void*, const cuuint64_t*, const cuuint64_t*,
                                    const cuuint32_t*, const cuuint32_t*, CUtensorMapInterleave, CUtensorMapSwizzle,
                                    CUtensorMapL2promotion, CUtensorMapFloatOOBfill);

bool make_tm(PFN_encodeTiled enc, CUtensorMap* tm, const void* base, int rank, const uint64_t* dims, const uint64_t* strides,
             const uint32_t* box, CUtensorMapSwizzle sw) {
  cuuint64_t gd[5], gs[5];
  cuuint32_t bx[5], es[5];
  for (int i = 0; i < rank; i++) { gd[i] = dims[i]; bx[i] = box[i]; es[i] = 1; }
  for (int i = 0; i + 1 < rank; i++) gs[i] = strides[i];
  return enc(tm, CU_TENSOR_MAP_DATA_TYPE_BFLOAT16, rank, const_cast<void*>(base), gd, gs, bx, es, CU_TENSOR_MAP_INTERLEAVE_NONE, sw,
             CU_TENSOR_MAP_L2_PROMOTION_L2_256B, CU_TENSOR_MAP_FLOAT_OOB_FILL_NONE) == CUDA_SUCCESS;
}
bool make_tm2(PFN_encodeTiled enc, CUtensorMap* tm, const void* base, uint64_t inner, uint64_t outer, uint32_t b0, uint32_t b1,
              CUtensorMapSwizzle sw = CU_TENSOR_MAP_SWIZZLE_128B) {
  const uint64_t dims[2] = {inner, outer}, str[1] = {inner * 2};
  const uint32_t box[2] = {b0, b1};
  return make_tm(enc, tm, base, 2, dims, str, box, sw);
}

}

extern "C" void kernel_launch(void* const* d_in, const int* in_sizes, int n_in, void* d_out, int out_size) {
  (void)in_sizes; (void)n_in; (void)out_size;
  static PFN_encodeTiled enc = nullptr;
  static void *pHT = nullptr, *pO = nullptr;
  if (!enc) {
    void* fn = nullptr;
    cudaDriverEntryPointQueryResult qr;
    if (cudaGetDriverEntryPoint("cuTensorMapEncodeTiled", &fn, cudaEnableDefault, &qr) != cudaSuccess || !fn) return;
    enc = (PFN_encodeTiled)fn;
    cudaFuncSetAttribute(fused_kernel, cudaFuncAttributeMaxDynamicSharedMemorySize, SMEM_BYTES);
    cudaGetSymbolAddress(&pHT, g_HT);
    cudaGetSymbolAddress(&pO, g_O);
  }
  Params prm;
  bool ok = true;
  {
    const uint64_t dims[5] = {1024, 2, 4, 16, 16}, str[4] = {2048, 65536, 4096, 262144};
    const uint32_t box[5] = {64, 2, 4, 16, 1};
    ok &= make_tm(enc, &prm.tmXB, d_in[4], 5, dims, str, box, CU_TENSOR_MAP_SWIZZLE_128B);
  }
  ok &= make_tm2(enc, &prm.tmBre, d_in[7], 1024, 1024, 64, 64);
  ok &= make_tm2(enc, &prm.tmBim, d_in[8], 1024, 1024, 64, 64);
  ok &= make_tm2(enc, &prm.tmXA, d_in[0], 1024, 2048, 64, 128);
  ok &= make_tm2(enc, &prm.tmWqkv, d_in[1], 3072, 1024, 64, 64);
  ok &= make_tm2(enc, &prm.tmWphi, d_in[2], 32, 1024, 32, 64, CU_TENSOR_MAP_SWIZZLE_64B);
  {
    const uint64_t dims[3] = {64, 2048, 32}, str[2] = {4096, 128};
    const uint32_t box[3] = {64, 64, 2};
    ok &= make_tm(enc, &prm.tmHT, pHT, 3, dims, str, box, CU_TENSOR_MAP_SWIZZLE_128B);
  }
  {
    const uint64_t dims[3] = {64, 2048, 32}, str[2] = {4096, 128};
    const uint32_t box[3] = {64, 16, 1};
    ok &= make_tm(enc, &prm.tmHTs, pHT, 3, dims, str, box, CU_TENSOR_MAP_SWIZZLE_128B);
  }
  ok &= make_tm2(enc, &prm.tmCre, d_in[9], 1024, 1024, 64, 64);
  ok &= make_tm2(enc, &prm.tmCim, d_in[10], 1024, 1024, 64, 64);
  ok &= make_tm2(enc, &prm.tmO, pO, 1024, 2048, 64, 128);
  ok &= make_tm2(enc, &prm.tmWo, d_in[3], 1024, 1024, 64, 64);
  if (!ok) return;
  prm.xB = (const __nv_bfloat16*)d_in[4];
  prm.lam_re = (const __nv_bfloat16*)d_in[5];
  prm.lam_im = (const __nv_bfloat16*)d_in[6];
  prm.log_dt = (const __nv_bfloat16*)d_in[11];
  prm.dskip = (const __nv_bfloat16*)d_in[12];
  prm.out = (float*)d_out;

  cudaLaunchConfig_t cfg = {};
  cfg.gridDim = dim3(128);
  cfg.blockDim = dim3(384);
  cfg.dynamicSmemBytes = SMEM_BYTES;
  cfg.stream = cudaStreamPerThread;
  cudaLaunchAttribute attr[1];
  attr[0].id = cudaLaunchAttributeClusterDimension;
  attr[0].val.clusterDim.x = 2; attr[0].val.clusterDim.y = 1; attr[0].val.clusterDim.z = 1;
  cfg.attrs = attr;
  cfg.numAttrs = 1;
  cudaLaunchKernelEx(&cfg, fused_kernel, prm);
}
```

```cpp
#include <cuda_runtime.h>
#include <cuda_bf16.h>
#include <cuda.h>
#include <stdint.h>
#include <type_traits>

namespace {

constexpr int SEQ = 2048;
constexpr int DM = 1024;
constexpr int STAGES = 5;
constexpr int STAGE_BYTES = 32768;
constexpr int OFF_EB = STAGES * STAGE_BYTES;
constexpr int OFF_PHI = OFF_EB;
constexpr int OFF_V = OFF_EB + 32768;
constexpr int OFF_WPHI = OFF_EB + 53248;
constexpr int OFF_ONES = OFF_EB + 61440;
constexpr int OFF_BAR = OFF_EB + 62464;
constexpr int SMEM_BYTES = OFF_BAR + 512 + 1024;
constexpr int B_EMPTY = 64, B_ORD = 128  , B_WPHI = 144, B_EPOCH = 152, B_PARAM = 160, B_KVX = 168  , B_EBA = 184  ,
              B_EPOCHV = 200, B_DEAD = 204, B_JOB = 208  , B_EBF = 256  ;

constexpr int KVW = 40;

struct Params {
  CUtensorMap tmXB;
  CUtensorMap tmBre, tmBim;
  CUtensorMap tmXA;
  CUtensorMap tmWqkv;
  CUtensorMap tmWphi;
  CUtensorMap tmHT;
  CUtensorMap tmHTs;
  CUtensorMap tmCre, tmCim;
  CUtensorMap tmO;
  CUtensorMap tmWo;
  const __nv_bfloat16* xB;
  const __nv_bfloat16* lam_re;
  const __nv_bfloat16* lam_im;
  const __nv_bfloat16* log_dt;
  const __nv_bfloat16* dskip;
  float* out;
};

__device__ __nv_bfloat16 g_HT[2048 * 2048];
__device__ __nv_bfloat16 g_O[SEQ * DM];
__device__ float g_kv[32 * 64 * KVW];
__device__ uint4 g_E[16 * 16 * 64];
struct Flags {
  unsigned ticket;   unsigned pad0[31];
  unsigned zero_cnt; unsigned pad1[31];
  unsigned hcnt[16 * 8];
  unsigned kvcnt[16 * 8];
  unsigned ocnt[2 * 16 * 8];
};
__device__ Flags g_flags;

__device__ __forceinline__ uint32_t smem_u32(const void* p) { return (uint32_t)__cvta_generic_to_shared(p); }
__device__ __forceinline__ void mbar_init(uint32_t bar, uint32_t count) {
  asm volatile("mbarrier.init.shared::cta.b64 [%0], %1;" ::"r"(bar), "r"(count));
}
__device__ __forceinline__ void mbar_expect_tx(uint32_t bar, uint32_t bytes) {
  asm volatile("mbarrier.arrive.expect_tx.shared::cta.b64 _, [%0], %1;" ::"r"(bar), "r"(bytes) : "memory");
}
__device__ __forceinline__ void mbar_arrive(uint32_t bar) {
  asm volatile("mbarrier.arrive.shared::cta.b64 _, [%0];" ::"r"(bar) : "memory");
}
__device__ __forceinline__ void mbar_arrive_cluster(uint32_t bar, uint32_t cta) {
  asm volatile("{\n.reg .b32 ra;\nmapa.shared::cluster.u32 ra, %0, %1;\nmbarrier.arrive.shared::cluster.b64 _, [ra];\n}" ::"r"(bar), "r"(cta) : "memory");
}
__device__ __forceinline__ uint32_t dead_addr(uint32_t bar) { return (bar & ~0x1FFu) + B_DEAD; }
__device__ __forceinline__ void mbar_wait(uint32_t bar, uint32_t parity) {
  asm volatile(
      "{\n.reg .pred p;\n.reg .u32 c, d;\n"
      "mov.u32 c, 0;\n"
      "WAIT_LOOP:\n"
      "mbarrier.try_wait.parity.shared::cta.b64 p, [%0], %1;\n"
      "@p bra WAIT_DONE;\n"
      "add.u32 c, c, 1;\n"
      "setp.gt.u32 p, c, 0x200000;\n"
      "@p st.volatile.shared.u32 [%2], c;\n"
      "ld.volatile.shared.u32 d, [%2];\n"
      "setp.eq.u32 p, d, 0;\n"
      "@p bra WAIT_LOOP;\n"
      "WAIT_DONE:\n}\n" ::"r"(bar), "r"(parity), "r"(dead_addr(bar)) : "memory");
}
__device__ __forceinline__ void mbar_wait_long(uint32_t bar, uint32_t parity) {
  asm volatile(
      "{\n.reg .pred p;\n.reg .u32 c, d;\n"
      "mov.u32 c, 0;\n"
      "WAITL_LOOP:\n"
      "mbarrier.try_wait.parity.shared::cta.b64 p, [%0], %1;\n"
      "@p bra WAITL_DONE;\n"
      "nanosleep.u32 100;\n"
      "add.u32 c, c, 1;\n"
      "setp.gt.u32 p, c, 0x200000;\n"
      "@p st.volatile.shared.u32 [%2], c;\n"
      "ld.volatile.shared.u32 d, [%2];\n"
      "setp.eq.u32 p, d, 0;\n"
      "@p bra WAITL_LOOP;\n"
      "WAITL_DONE:\n}\n" ::"r"(bar), "r"(parity), "r"(dead_addr(bar)) : "memory");
}
__device__ __forceinline__ bool give_up(uint32_t bars, unsigned spins) {
  unsigned d;
  if (spins > (1u << 20)) asm volatile("st.volatile.shared.u32 [%0], %1;" ::"r"(bars + B_DEAD), "r"(spins) : "memory");
  asm volatile("ld.volatile.shared.u32 %0, [%1];" : "=r"(d) : "r"(bars + B_DEAD) : "memory");
  return d != 0;
}
__device__ __forceinline__ unsigned ld_relaxed(const unsigned* p) {
  unsigned v;
  asm volatile("ld.relaxed.gpu.global.u32 %0, [%1];" : "=r"(v) : "l"(p) : "memory");
  return v;
}
__device__ __forceinline__ void wait_ge(uint32_t bars, const unsigned* p, unsigned target) {
  unsigned spins = 0;
  while ((int)(ld_relaxed(p) - target) < 0) {
    __nanosleep(128);
    if (give_up(bars, ++spins)) break;
  }
  asm volatile("{\n.reg .u32 v;\nld.acquire.gpu.global.u32 v, [%0];\n}" ::"l"(p) : "memory");
}
__device__ __forceinline__ void red_release_add(unsigned* p, unsigned v) {
  asm volatile("red.release.gpu.global.add.u32 [%0], %1;" ::"l"(p), "r"(v) : "memory");
}
__device__ __forceinline__ void red_relaxed_add(unsigned* p, unsigned v) {
  asm volatile("red.relaxed.gpu.global.add.u32 [%0], %1;" ::"l"(p), "r"(v) : "memory");
}
__device__ __forceinline__ void st_tagged(uint4* p, float a, float b, unsigned tag) {
  const unsigned long long w0 = ((unsigned long long)tag << 32) | __float_as_uint(a);
  const unsigned long long w1 = ((unsigned long long)tag << 32) | __float_as_uint(b);
  asm volatile("st.relaxed.gpu.global.v2.b64 [%0], {%1, %2};" ::"l"(p), "l"(w0), "l"(w1) : "memory");
}
__device__ __forceinline__ void bulk_commit() { asm volatile("cp.async.bulk.commit_group;" ::: "memory"); }
__device__ __forceinline__ void bulk_wait_read() { asm volatile("cp.async.bulk.wait_group.read 0;" ::: "memory"); }
__device__ __forceinline__ void bulk_wait_all() { asm volatile("cp.async.bulk.wait_group 0;" ::: "memory"); }
__device__ __forceinline__ void bulk_reduce_f32(float* dst, uint32_t src, uint32_t bytes) {
  asm volatile("cp.reduce.async.bulk.global.shared::cta.bulk_group.add.f32 [%0], [%1], %2;" ::"l"(dst), "r"(src), "r"(bytes) : "memory");
}
__device__ __forceinline__ void tma_store_3d(const CUtensorMap* tm, uint32_t src, int c0, int c1, int c2) {
  asm volatile("cp.async.bulk.tensor.3d.global.shared::cta.bulk_group [%0, {%2, %3, %4}], [%1];"
               ::"l"(tm), "r"(src), "r"(c0), "r"(c1), "r"(c2) : "memory");
}
__device__ __forceinline__ void fence_async_global() { asm volatile("fence.proxy.async.global;" ::: "memory"); }
__device__ __forceinline__ void fence_async_smem() { asm volatile("fence.proxy.async.shared::cta;" ::: "memory"); }
__device__ __forceinline__ void tma_2d(uint32_t dst, const CUtensorMap* tm, int c0, int c1, uint32_t bar) {
  asm volatile("cp.async.bulk.tensor.2d.shared::cluster.global.mbarrier::complete_tx::bytes [%0], [%1, {%3, %4}], [%2];"
               ::"r"(dst), "l"(tm), "r"(bar), "r"(c0), "r"(c1) : "memory");
}
__device__ __forceinline__ void tma_3d(uint32_t dst, const CUtensorMap* tm, int c0, int c1, int c2, uint32_t bar) {
  asm volatile("cp.async.bulk.tensor.3d.shared::cluster.global.mbarrier::complete_tx::bytes [%0], [%1, {%3, %4, %5}], [%2];"
               ::"r"(dst), "l"(tm), "r"(bar), "r"(c0), "r"(c1), "r"(c2) : "memory");
}
__device__ __forceinline__ void tma_5d(uint32_t dst, const CUtensorMap* tm, int c0, int c1, int c2, int c3, int c4, uint32_t bar) {
  asm volatile("cp.async.bulk.tensor.5d.shared::cluster.global.mbarrier::complete_tx::bytes [%0], [%1, {%3, %4, %5, %6, %7}], [%2];"
               ::"r"(dst), "l"(tm), "r"(bar), "r"(c0), "r"(c1), "r"(c2), "r"(c3), "r"(c4) : "memory");
}
__device__ __forceinline__ void tma_2d_mc(uint32_t dst, const CUtensorMap* tm, int c0, int c1, uint32_t bar) {
  asm volatile("cp.async.bulk.tensor.2d.shared::cluster.global.mbarrier::complete_tx::bytes.multicast::cluster [%0], [%1, {%3, %4}], [%2], %5;"
               ::"r"(dst), "l"(tm), "r"(bar), "r"(c0), "r"(c1), "h"((uint16_t)3) : "memory");
}
__device__ __forceinline__ void tma_store_2d(const CUtensorMap* tm, uint32_t src, int c0, int c1) {
  asm volatile("cp.async.bulk.tensor.2d.global.shared::cta.bulk_group [%0, {%2, %3}], [%1];"
               ::"l"(tm), "r"(src), "r"(c0), "r"(c1) : "memory");
}
__device__ __forceinline__ bool elect_one() {
  uint32_t p;
  asm volatile("{\n.reg .pred e;\nelect.sync _|e, 0xffffffff;\nselp.u32 %0, 1, 0, e;\n}" : "=r"(p));
  return p != 0;
}
__device__ __forceinline__ void prefetch_tm(const CUtensorMap* tm) {
  asm volatile("prefetch.tensormap [%0];" ::"l"(tm) : "memory");
}
__device__ __forceinline__ void wgmma_fence() { asm volatile("wgmma.fence.sync.aligned;" ::: "memory"); }
__device__ __forceinline__ void wgmma_commit() { asm volatile("wgmma.commit_group.sync.aligned;" ::: "memory"); }
template <int N> __device__ __forceinline__ void wgmma_wait() { asm volatile("wgmma.wait_group.sync.aligned %0;" ::"n"(N) : "memory"); }
__device__ __forceinline__ void wg_bar(int id) {
  if (id == 1) asm volatile("bar.sync 1, 128;" ::: "memory");
  else asm volatile("bar.sync 2, 128;" ::: "memory");
}
template <int R> __device__ __forceinline__ void reg_alloc() { asm volatile("setmaxnreg.inc.sync.aligned.u32 %0;" ::"n"(R)); }
template <int R> __device__ __forceinline__ void reg_dealloc() { asm volatile("setmaxnreg.dec.sync.aligned.u32 %0;" ::"n"(R)); }

__device__ __forceinline__ uint64_t make_desc(uint32_t saddr, uint32_t lbo_bytes, uint32_t sbo_bytes, uint32_t layout) {
  uint64_t d = (uint64_t)((saddr & 0x3FFFF) >> 4);
  d |= (uint64_t)((lbo_bytes & 0x3FFFF) >> 4) << 16;
  d |= (uint64_t)((sbo_bytes & 0x3FFFF) >> 4) << 32;
  d |= (uint64_t)layout << 62;
  return d;
}
__device__ __forceinline__ uint64_t desc128(uint32_t lo) { return ((uint64_t)0x40000040u << 32) | lo; }
__device__ __forceinline__ uint32_t pack_bf16(float lo, float hi) {
  uint32_t r;
  asm("cvt.rn.bf16x2.f32 %0, %1, %2;" : "=r"(r) : "f"(hi), "f"(lo));
  return r;
}
__device__ __forceinline__ float ex2(float x) { float y; asm("ex2.approx.ftz.f32 %0, %1;" : "=f"(y) : "f"(x)); return y; }
__device__ __forceinline__ float rcp(float x) { float y; asm("rcp.approx.ftz.f32 %0, %1;" : "=f"(y) : "f"(x)); return y; }
__device__ __forceinline__ void stmatrix_x4(uint32_t addr, uint32_t r0, uint32_t r1, uint32_t r2, uint32_t r3) {
  asm volatile("stmatrix.sync.aligned.m8n8.x4.shared.b16 [%0], {%1, %2, %3, %4};" ::"r"(addr), "r"(r0), "r"(r1), "r"(r2), "r"(r3) : "memory");
}
template <int N> __device__ __forceinline__ void fence_regs(float (&d)[N]) {
#pragma unroll
  for (int i = 0; i < N; i++) asm volatile("" : "+f"(d[i])::"memory");
}

template <int TA, int TB>
__device__ __forceinline__ void wgmma_m64n128k16_ss(float (&d)[64], uint64_t descA, uint64_t descB) {
  asm volatile("{\n.reg .pred p;\nsetp.ne.b32 p, 1, 0;\n"
    "wgmma.mma_async.sync.aligned.m64n128k16.f32.bf16.bf16 "
    "{%0, %1, %2, %3, %4, %5, %6, %7, %8, %9, %10, %11, %12, %13, %14, %15, %16, %17, %18, %19, %20, %21, %22, %23, %24, %25, %26, %27, %28, %29, %30, %31, %32, %33, %34, %35, %36, %37, %38, %39, %40, %41, %42, %43, %44, %45, %46, %47, %48, %49, %50, %51, %52, %53, %54, %55, %56, %57, %58, %59, %60, %61, %62, %63}, "
    "%64, %65, p, 1, 1, %66, %67;\n}\n"
    : "+f"(d[0]), "+f"(d[1]), "+f"(d[2]), "+f"(d[3]), "+f"(d[4]), "+f"(d[5]), "+f"(d[6]), "+f"(d[7]), "+f"(d[8]), "+f"(d[9]), "+f"(d[10]), "+f"(d[11]), "+f"(d[12]), "+f"(d[13]), "+f"(d[14]), "+f"(d[15]), "+f"(d[16]), "+f"(d[17]), "+f"(d[18]), "+f"(d[19]), "+f"(d[20]), "+f"(d[21]), "+f"(d[22]), "+f"(d[23]), "+f"(d[24]), "+f"(d[25]), "+f"(d[26]), "+f"(d[27]), "+f"(d[28]), "+f"(d[29]), "+f"(d[30]), "+f"(d[31]), "+f"(d[32]), "+f"(d[33]), "+f"(d[34]), "+f"(d[35]), "+f"(d[36]), "+f"(d[37]), "+f"(d[38]), "+f"(d[39]), "+f"(d[40]), "+f"(d[41]), "+f"(d[42]), "+f"(d[43]), "+f"(d[44]), "+f"(d[45]), "+f"(d[46]), "+f"(d[47]), "+f"(d[48]), "+f"(d[49]), "+f"(d[50]), "+f"(d[51]), "+f"(d[52]), "+f"(d[53]), "+f"(d[54]), "+f"(d[55]), "+f"(d[56]), "+f"(d[57]), "+f"(d[58]), "+f"(d[59]), "+f"(d[60]), "+f"(d[61]), "+f"(d[62]), "+f"(d[63])
    : "l"(descA), "l"(descB), "n"(TA), "n"(TB));
}

template <int TA, int TB>
__device__ __forceinline__ void wgmma_m64n32k16_ss(float (&d)[16], uint64_t descA, uint64_t descB) {
  asm volatile("{\n.reg .pred p;\nsetp.ne.b32 p, 1, 0;\n"
    "wgmma.mma_async.sync.aligned.m64n32k16.f32.bf16.bf16 "
    "{%0, %1, %2, %3, %4, %5, %6, %7, %8, %9, %10, %11, %12, %13, %14, %15}, "
    "%16, %17, p, 1, 1, %18, %19;\n}\n"
    : "+f"(d[0]), "+f"(d[1]), "+f"(d[2]), "+f"(d[3]), "+f"(d[4]), "+f"(d[5]), "+f"(d[6]), "+f"(d[7]), "+f"(d[8]), "+f"(d[9]), "+f"(d[10]), "+f"(d[11]), "+f"(d[12]), "+f"(d[13]), "+f"(d[14]), "+f"(d[15])
    : "l"(descA), "l"(descB), "n"(TA), "n"(TB));
}

template <int TA, int TB>
__device__ __forceinline__ void wgmma_m64n32k16_ss_init(float (&d)[16], uint64_t descA, uint64_t descB) {
  asm volatile("{\n.reg .pred p;\nsetp.ne.b32 p, 0, 0;\n"
    "wgmma.mma_async.sync.aligned.m64n32k16.f32.bf16.bf16 "
    "{%0, %1, %2, %3, %4, %5, %6, %7, %8, %9, %10, %11, %12, %13, %14, %15}, "
    "%16, %17, p, 1, 1, %18, %19;\n}\n"
    : "=f"(d[0]), "=f"(d[1]), "=f"(d[2]), "=f"(d[3]), "=f"(d[4]), "=f"(d[5]), "=f"(d[6]), "=f"(d[7]), "=f"(d[8]), "=f"(d[9]), "=f"(d[10]), "=f"(d[11]), "=f"(d[12]), "=f"(d[13]), "=f"(d[14]), "=f"(d[15])
    : "l"(descA), "l"(descB), "n"(TA), "n"(TB));
}

template <int TB>
__device__ __forceinline__ void wgmma_m64n32k16_rs(float (&d)[16], uint32_t a0, uint32_t a1, uint32_t a2, uint32_t a3, uint64_t descB) {
  asm volatile("{\n.reg .pred p;\nsetp.ne.b32 p, 1, 0;\n"
    "wgmma.mma_async.sync.aligned.m64n32k16.f32.bf16.bf16 "
    "{%0, %1, %2, %3, %4, %5, %6, %7, %8, %9, %10, %11, %12, %13, %14, %15}, "
    "{%16, %17, %18, %19}, %20, p, 1, 1, %21;\n}\n"
    : "+f"(d[0]), "+f"(d[1]), "+f"(d[2]), "+f"(d[3]), "+f"(d[4]), "+f"(d[5]), "+f"(d[6]), "+f"(d[7]), "+f"(d[8]), "+f"(d[9]), "+f"(d[10]), "+f"(d[11]), "+f"(d[12]), "+f"(d[13]), "+f"(d[14]), "+f"(d[15])
    : "r"(a0), "r"(a1), "r"(a2), "r"(a3), "l"(descB), "n"(TB));
}

template <int TB>
__device__ __forceinline__ void wgmma_m64n32k16_rs_init(float (&d)[16], uint32_t a0, uint32_t a1, uint32_t a2, uint32_t a3, uint64_t descB) {
  asm volatile("{\n.reg .pred p;\nsetp.ne.b32 p, 0, 0;\n"
    "wgmma.mma_async.sync.aligned.m64n32k16.f32.bf16.bf16 "
    "{%0, %1, %2, %3, %4, %5, %6, %7, %8, %9, %10, %11, %12, %13, %14, %15}, "
    "{%16, %17, %18, %19}, %20, p, 1, 1, %21;\n}\n"
    : "=f"(d[0]), "=f"(d[1]), "=f"(d[2]), "=f"(d[3]), "=f"(d[4]), "=f"(d[5]), "=f"(d[6]), "=f"(d[7]), "=f"(d[8]), "=f"(d[9]), "=f"(d[10]), "=f"(d[11]), "=f"(d[12]), "=f"(d[13]), "=f"(d[14]), "=f"(d[15])
    : "r"(a0), "r"(a1), "r"(a2), "r"(a3), "l"(descB), "n"(TB));
}

template <int TA, int TB>
__device__ __forceinline__ void wgmma_m64n40k16_ss(float (&d)[20], uint64_t descA, uint64_t descB) {
  asm volatile("{\n.reg .pred p;\nsetp.ne.b32 p, 1, 0;\n"
    "wgmma.mma_async.sync.aligned.m64n40k16.f32.bf16.bf16 "
    "{%0, %1, %2, %3, %4, %5, %6, %7, %8, %9, %10, %11, %12, %13, %14, %15, %16, %17, %18, %19}, "
    "%20, %21, p, 1, 1, %22, %23;\n}\n"
    : "+f"(d[0]), "+f"(d[1]), "+f"(d[2]), "+f"(d[3]), "+f"(d[4]), "+f"(d[5]), "+f"(d[6]), "+f"(d[7]), "+f"(d[8]), "+f"(d[9]), "+f"(d[10]), "+f"(d[11]), "+f"(d[12]), "+f"(d[13]), "+f"(d[14]), "+f"(d[15]), "+f"(d[16]), "+f"(d[17]), "+f"(d[18]), "+f"(d[19])
    : "l"(descA), "l"(descB), "n"(TA), "n"(TB));
}

template <int TA, int TB>
__device__ __forceinline__ void wgmma_m64n40k16_ss_init(float (&d)[20], uint64_t descA, uint64_t descB) {
  asm volatile("{\n.reg .pred p;\nsetp.ne.b32 p, 0, 0;\n"
    "wgmma.mma_async.sync.aligned.m64n40k16.f32.bf16.bf16 "
    "{%0, %1, %2, %3, %4, %5, %6, %7, %8, %9, %10, %11, %12, %13, %14, %15, %16, %17, %18, %19}, "
    "%20, %21, p, 1, 1, %22, %23;\n}\n"
    : "=f"(d[0]), "=f"(d[1]), "=f"(d[2]), "=f"(d[3]), "=f"(d[4]), "=f"(d[5]), "=f"(d[6]), "=f"(d[7]), "=f"(d[8]), "=f"(d[9]), "=f"(d[10]), "=f"(d[11]), "=f"(d[12]), "=f"(d[13]), "=f"(d[14]), "=f"(d[15]), "=f"(d[16]), "=f"(d[17]), "=f"(d[18]), "=f"(d[19])
    : "l"(descA), "l"(descB), "n"(TA), "n"(TB));
}

template <int TB>
__device__ __forceinline__ void wgmma_m64n40k16_rs(float (&d)[20], uint32_t a0, uint32_t a1, uint32_t a2, uint32_t a3, uint64_t descB) {
  asm volatile("{\n.reg .pred p;\nsetp.ne.b32 p, 1, 0;\n"
    "wgmma.mma_async.sync.aligned.m64n40k16.f32.bf16.bf16 "
    "{%0, %1, %2, %3, %4, %5, %6, %7, %8, %9, %10, %11, %12, %13, %14, %15, %16, %17, %18, %19}, "
    "{%20, %21, %22, %23}, %24, p, 1, 1, %25;\n}\n"
    : "+f"(d[0]), "+f"(d[1]), "+f"(d[2]), "+f"(d[3]), "+f"(d[4]), "+f"(d[5]), "+f"(d[6]), "+f"(d[7]), "+f"(d[8]), "+f"(d[9]), "+f"(d[10]), "+f"(d[11]), "+f"(d[12]), "+f"(d[13]), "+f"(d[14]), "+f"(d[15]), "+f"(d[16]), "+f"(d[17]), "+f"(d[18]), "+f"(d[19])
    : "r"(a0), "r"(a1), "r"(a2), "r"(a3), "l"(descB), "n"(TB));
}

template <int TB>
__device__ __forceinline__ void wgmma_m64n40k16_rs_init(float (&d)[20], uint32_t a0, uint32_t a1, uint32_t a2, uint32_t a3, uint64_t descB) {
  asm volatile("{\n.reg .pred p;\nsetp.ne.b32 p, 0, 0;\n"
    "wgmma.mma_async.sync.aligned.m64n40k16.f32.bf16.bf16 "
    "{%0, %1, %2, %3, %4, %5, %6, %7, %8, %9, %10, %11, %12, %13, %14, %15, %16, %17, %18, %19}, "
    "{%20, %21, %22, %23}, %24, p, 1, 1, %25;\n}\n"
    : "=f"(d[0]), "=f"(d[1]), "=f"(d[2]), "=f"(d[3]), "=f"(d[4]), "=f"(d[5]), "=f"(d[6]), "=f"(d[7]), "=f"(d[8]), "=f"(d[9]), "=f"(d[10]), "=f"(d[11]), "=f"(d[12]), "=f"(d[13]), "=f"(d[14]), "=f"(d[15]), "=f"(d[16]), "=f"(d[17]), "=f"(d[18]), "=f"(d[19])
    : "r"(a0), "r"(a1), "r"(a2), "r"(a3), "l"(descB), "n"(TB));
}


template <int MODE>
__device__ __forceinline__ void mainloop(float (&acc0)[64], float (&acc1)[64], int it0, int nkb, uint32_t sbase, int cw,
                                         uint32_t ord_parity) {
  const uint32_t bars = sbase + OFF_BAR;
  const int lane = threadIdx.x & 31;
  int stage = it0 % STAGES;
  uint32_t phase = (it0 / STAGES) & 1;
#pragma unroll
  for (int i = 0; i < 64; i++) { acc0[i] = 0.f; acc1[i] = 0.f; }
  mbar_wait(bars + B_ORD + 8 * cw, ord_parity);
  int prev = 0;
  for (int kb = 0; kb < nkb; kb++) {
    mbar_wait(bars + 8 * stage, phase);
    const uint32_t lo = ((sbase & 0x3FFFFu) + stage * STAGE_BYTES) >> 4;
    const uint32_t loK = lo | (1u << 16), loM = lo | (512u << 16);
    wgmma_fence();
#pragma unroll
    for (int k = 0; k < 4; k++) {
      if (MODE == 0) {
        const uint64_t dx = desc128(loK + 1024 + 2 * k);
        wgmma_m64n128k16_ss<0, 0>(acc0, desc128(loK + 2 * k), dx);
        wgmma_m64n128k16_ss<0, 0>(acc1, desc128(loK + 512 + 2 * k), dx);
      } else if (MODE == 1) {
        const uint64_t dw = desc128(loM + 128 * k);
        wgmma_m64n128k16_ss<0, 1>(acc0, desc128(loK + 1024 + 2 * k), dw);
        wgmma_m64n128k16_ss<0, 1>(acc1, desc128(loK + 1536 + 2 * k), dw);
      } else {
        const uint64_t dw = desc128(loK + 2 * k);
        wgmma_m64n128k16_ss<1, 0>(acc0, desc128(loM + 1024 + 128 * k), dw);
        wgmma_m64n128k16_ss<1, 0>(acc1, desc128(loM + 1536 + 128 * k), dw);
      }
      if (k == 1 && kb == nkb - 1 && (threadIdx.x & 127) == 0) mbar_arrive(bars + B_ORD + 8 * (cw ^ 1));
    }
    wgmma_commit();
    wgmma_wait<1>();
    if (kb > 0 && lane < 2) mbar_arrive_cluster(bars + B_EMPTY + 8 * prev, lane);
    prev = stage;
    if (++stage == STAGES) { stage = 0; phase ^= 1; }
  }
  wgmma_wait<0>();
  if (lane < 2) mbar_arrive_cluster(bars + B_EMPTY + 8 * prev, lane);
  fence_regs(acc0);
  fence_regs(acc1);
}

template <int N>
__device__ __forceinline__ void dual_softmax_n(const float (&p)[N][16], uint32_t (&pos)[N][8], uint32_t (&neg)[N][8]) {
  constexpr float L2E = 1.4426950408889634f;
  float ca[N][2], cb[N][2];
  {
    float mx[N][2], mn[N][2];
#pragma unroll
    for (int i = 0; i < N; i++)
#pragma unroll
      for (int r = 0; r < 2; r++) {
        const int o = 2 * r;
        mx[i][r] = fmaxf(fmaxf(fmaxf(p[i][o], p[i][o + 1]), fmaxf(p[i][4 + o], p[i][5 + o])),
                         fmaxf(fmaxf(p[i][8 + o], p[i][9 + o]), fmaxf(p[i][12 + o], p[i][13 + o])));
        mn[i][r] = fminf(fminf(fminf(p[i][o], p[i][o + 1]), fminf(p[i][4 + o], p[i][5 + o])),
                         fminf(fminf(p[i][8 + o], p[i][9 + o]), fminf(p[i][12 + o], p[i][13 + o])));
      }
#pragma unroll
    for (int o = 1; o <= 2; o <<= 1) {
      float tx[N][2], tn[N][2];
#pragma unroll
      for (int i = 0; i < N; i++)
#pragma unroll
        for (int r = 0; r < 2; r++) { tx[i][r] = __shfl_xor_sync(0xffffffffu, mx[i][r], o); tn[i][r] = __shfl_xor_sync(0xffffffffu, mn[i][r], o); }
#pragma unroll
      for (int i = 0; i < N; i++)
#pragma unroll
        for (int r = 0; r < 2; r++) { mx[i][r] = fmaxf(mx[i][r], tx[i][r]); mn[i][r] = fminf(mn[i][r], tn[i][r]); }
    }
#pragma unroll
    for (int i = 0; i < N; i++)
#pragma unroll
      for (int r = 0; r < 2; r++) { ca[i][r] = -mx[i][r] * L2E; cb[i][r] = mn[i][r] * L2E; }
  }
  float ep[2][16], en[2][16];
  float rp[2], rn[2];
#pragma unroll
  for (int i = 0; i <= N; i++) {
    const int cur = i & 1, prv = cur ^ 1;
    if (i > 0) {
      float sp[2], sn[2];
#pragma unroll
      for (int r = 0; r < 2; r++) {
        const int o = 2 * r;
        sp[r] = ((ep[prv][o] + ep[prv][o + 1]) + (ep[prv][4 + o] + ep[prv][5 + o])) + ((ep[prv][8 + o] + ep[prv][9 + o]) + (ep[prv][12 + o] + ep[prv][13 + o]));
        sn[r] = ((en[prv][o] + en[prv][o + 1]) + (en[prv][4 + o] + en[prv][5 + o])) + ((en[prv][8 + o] + en[prv][9 + o]) + (en[prv][12 + o] + en[prv][13 + o]));
      }
      float t0[2], t1[2];
#pragma unroll
      for (int r = 0; r < 2; r++) { t0[r] = __shfl_xor_sync(0xffffffffu, sp[r], 1); t1[r] = __shfl_xor_sync(0xffffffffu, sn[r], 1); }
      if (i < N) {
#pragma unroll
        for (int e = 0; e < 4; e++) {
          ep[cur][e] = ex2(fmaf(p[i][e], L2E, ca[i][e >> 1])); en[cur][e] = ex2(fmaf(p[i][e], -L2E, cb[i][e >> 1]));
        }
      }
#pragma unroll
      for (int r = 0; r < 2; r++) { sp[r] += t0[r]; sn[r] += t1[r]; }
#pragma unroll
      for (int r = 0; r < 2; r++) { t0[r] = __shfl_xor_sync(0xffffffffu, sp[r], 2); t1[r] = __shfl_xor_sync(0xffffffffu, sn[r], 2); }
      if (i < N) {
#pragma unroll
        for (int e = 4; e < 8; e++) {
          ep[cur][e] = ex2(fmaf(p[i][e], L2E, ca[i][(e >> 1) & 1])); en[cur][e] = ex2(fmaf(p[i][e], -L2E, cb[i][(e >> 1) & 1]));
        }
      }
#pragma unroll
      for (int r = 0; r < 2; r++) { rp[r] = rcp(sp[r] + t0[r]); rn[r] = rcp(sn[r] + t1[r]); }
    } else {
#pragma unroll
      for (int e = 0; e < 8; e++) {
        ep[cur][e] = ex2(fmaf(p[i][e], L2E, ca[i][(e >> 1) & 1])); en[cur][e] = ex2(fmaf(p[i][e], -L2E, cb[i][(e >> 1) & 1]));
      }
    }
#pragma unroll
    for (int j = 0; j < 4; j++) {
      if (i < N && j >= 2) {
#pragma unroll
        for (int e = 4 * j; e < 4 * j + 4; e++) {
          ep[cur][e] = ex2(fmaf(p[i][e], L2E, ca[i][(e >> 1) & 1])); en[cur][e] = ex2(fmaf(p[i][e], -L2E, cb[i][(e >> 1) & 1]));
        }
      }
      if (i > 0) {
#pragma unroll
        for (int r = 0; r < 2; r++) {
          pos[i - 1][2 * j + r] = pack_bf16(ep[prv][4 * j + 2 * r] * rp[r], ep[prv][4 * j + 2 * r + 1] * rp[r]);
          neg[i - 1][2 * j + r] = pack_bf16(en[prv][4 * j + 2 * r] * rn[r], en[prv][4 * j + 2 * r + 1] * rn[r]);
        }
      }
    }
  }
}

__device__ __forceinline__ float4 lds128(uint32_t addr) {
  float4 v;
  asm volatile("ld.shared.v4.f32 {%0, %1, %2, %3}, [%4];" : "=f"(v.x), "=f"(v.y), "=f"(v.z), "=f"(v.w) : "r"(addr) : "memory");
  return v;
}
__device__ __forceinline__ float2 lds64(uint32_t addr) {
  float2 v;
  asm volatile("ld.shared.v2.f32 {%0, %1}, [%2];" : "=f"(v.x), "=f"(v.y) : "r"(addr) : "memory");
  return v;
}
__device__ __forceinline__ void sts128(uint32_t addr, float a, float b, float c, float d) {
  asm volatile("st.shared.v4.f32 [%0], {%1, %2, %3, %4};" ::"r"(addr), "f"(a), "f"(b), "f"(c), "f"(d) : "memory");
}
struct cplx { float r, i; };
__device__ __forceinline__ cplx cmul(cplx a, cplx b) { return {a.r * b.r - a.i * b.i, a.r * b.i + a.i * b.r}; }
__device__ __forceinline__ cplx cfma(cplx a, cplx b, cplx c) {
  return {fmaf(a.r, b.r, fmaf(-a.i, b.i, c.r)), fmaf(a.r, b.i, fmaf(a.i, b.r, c.i))};
}
__device__ __forceinline__ cplx shfl_up_c(cplx v, int d) {
  return {__shfl_up_sync(0xffffffffu, v.r, d, 4), __shfl_up_sync(0xffffffffu, v.i, d, 4)};
}

struct ChanParams { cplx lam, c2, l32, l64, l128, g32, f512; };
constexpr int PSTRIDE = 80;

__device__ __forceinline__ void chan_params(float lr, float li, float log_dt, uint32_t dst) {
  const float dt = __bfloat162float(__float2bfloat16(expf(log_dt)));
  const float mag = expf(dt * lr);
  float sn, cs;
  sincosf(dt * li, &sn, &cs);
  const cplx lam = {mag * cs, mag * sn};
  const float nr = lam.r - 1.0f, ni = lam.i;
  const float den = lr * lr + li * li;
  const cplx c2 = {2.0f * (nr * lr + ni * li) / den, 2.0f * (ni * lr - nr * li) / den};
  cplx l = lam;
#pragma unroll 1
  for (int s = 0; s < 5; s++) l = cmul(l, l);
  const cplx l32 = l, l64 = cmul(l32, l32), l96 = cmul(l64, l32), l128 = cmul(l64, l64);
  const cplx l256 = cmul(l128, l128), l512 = cmul(l256, l256), l1024 = cmul(l512, l512), l1536 = cmul(l1024, l512);
  sts128(dst, lam.r, lam.i, c2.r, c2.i);
  sts128(dst + 16, l32.r, l32.i, l64.r, l64.i);
  sts128(dst + 32, l96.r, l96.i, l128.r, l128.i);
  sts128(dst + 48, l512.r, l512.i, l1024.r, l1024.i);
  sts128(dst + 64, l1536.r, l1536.i, 1.0f, 0.0f);
}
__device__ __forceinline__ ChanParams load_params(uint32_t src, int q) {
  ChanParams c;
  const float4 a = lds128(src), b = lds128(src + 16), d = lds128(src + 32);
  c.lam = {a.x, a.y}; c.c2 = {a.z, a.w}; c.l32 = {b.x, b.y}; c.l64 = {b.z, b.w}; c.l128 = {d.z, d.w};
  const float2 g = lds64(src + (q == 0 ? 72 : 8 + 8 * q)), f = lds64(src + (q == 0 ? 72 : 40 + 8 * q));
  c.g32 = {g.x, g.y}; c.f512 = {f.x, f.y};
  return c;
}

__device__ __forceinline__ void epi_bu(float (&are)[64], float (&aim)[64], const ChanParams (&cp)[2],
                                       uint32_t sbase, int G, int chunk, int cw, unsigned epoch) {
  const int lane = threadIdx.x & 31, w = (threadIdx.x & 127) >> 5, q = lane & 3, r8 = lane >> 2;
  cplx E[2] = {{0.f, 0.f}, {0.f, 0.f}};
#pragma unroll
  for (int k8 = 0; k8 < 16; k8++)
#pragma unroll
    for (int e = 0; e < 2; e++)
#pragma unroll
      for (int c = 0; c < 2; c++) E[c] = cfma(cp[c].lam, E[c], cplx{are[4 * k8 + 2 * c + e], aim[4 * k8 + 2 * c + e]});
  cplx prev[2];
#pragma unroll
  for (int c = 0; c < 2; c++) {
    cplx t = shfl_up_c(E[c], 1);
    if (q >= 1) E[c] = cfma(cp[c].l32, t, E[c]);
    t = shfl_up_c(E[c], 2);
    if (q >= 2) E[c] = cfma(cp[c].l64, t, E[c]);
    prev[c] = shfl_up_c(E[c], 1);
    if (q == 0) prev[c] = {0.f, 0.f};
  }
  uint4* gE = g_E + (size_t)G * 16 * 64 + 16 * w + r8;
  if (q == 3) {
    st_tagged(gE + chunk * 64, E[0].r, E[0].i, epoch);
    st_tagged(gE + chunk * 64 + 8, E[1].r, E[1].i, epoch);
  }
  cplx V[2][4];
  {
    unsigned long long w0[8], w1[8];
    unsigned pending = 0;
#pragma unroll
    for (int i = 0; i < 8; i++) {
      w0[i] = 0ull; w1[i] = 0ull;
      if (chunk - 1 - 4 * q - (i & 3) >= 0) pending |= 1u << i;
    }
    unsigned spins = 0;
    if (chunk > 0) __nanosleep(1000);
    while (true) {
#pragma unroll
      for (int i = 0; i < 8; i++)
        asm volatile("{\n.reg .pred p;\nsetp.ne.u32 p, %3, 0;\n@p ld.relaxed.gpu.global.v2.b64 {%0, %1}, [%2];\n}"
                     : "+l"(w0[i]), "+l"(w1[i]) : "l"(gE + (chunk - 1 - 4 * q - (i & 3)) * 64 + 8 * (i >> 2)), "r"(pending & (1u << i)) : "memory");
#pragma unroll
      for (int i = 0; i < 8; i++)
        if ((unsigned)(w0[i] >> 32) == epoch && (unsigned)(w1[i] >> 32) == epoch) pending &= ~(1u << i);
      if (__all_sync(0xffffffffu, pending == 0)) break;
      __nanosleep(500);
      if (give_up(sbase + OFF_BAR, ++spins)) break;
    }
#pragma unroll
    for (int i = 0; i < 8; i++) V[i >> 2][i & 3] = {__uint_as_float((unsigned)w0[i]), __uint_as_float((unsigned)w1[i])};
  }
  cplx s[2];
#pragma unroll
  for (int c = 0; c < 2; c++) {
    cplx Pq = V[c][3];
#pragma unroll
    for (int jj = 2; jj >= 0; jj--) Pq = cfma(cp[c].l128, Pq, V[c][jj]);
    Pq = cmul(Pq, cp[c].f512);
#pragma unroll
    for (int o = 1; o <= 2; o <<= 1) {
      Pq.r += __shfl_xor_sync(0xffffffffu, Pq.r, o);
      Pq.i += __shfl_xor_sync(0xffffffffu, Pq.i, o);
    }
    s[c] = cfma(cp[c].g32, Pq, prev[c]);
  }
  if (cw == 1) mbar_wait(sbase + OFF_BAR + B_EBF, 0);
#pragma unroll
  for (int qq = 0; qq < 4; qq++) {
    uint32_t ore[2][4], oim[2][4];
#pragma unroll
    for (int kk = 0; kk < 4; kk++) {
      const int k8 = 4 * qq + kk;
      float hr[2][2], hi[2][2];
#pragma unroll
      for (int e = 0; e < 2; e++)
#pragma unroll
        for (int c = 0; c < 2; c++) {
          s[c] = cfma(cp[c].lam, s[c], cplx{are[4 * k8 + 2 * c + e], aim[4 * k8 + 2 * c + e]});
          hr[c][e] = fmaf(cp[c].c2.r, s[c].r, -cp[c].c2.i * s[c].i);
          hi[c][e] = -fmaf(cp[c].c2.r, s[c].i, cp[c].c2.i * s[c].r);
        }
#pragma unroll
      for (int c = 0; c < 2; c++) {
        ore[c][kk] = pack_bf16(hr[c][0], hr[c][1]);
        oim[c][kk] = pack_bf16(hi[c][0], hi[c][1]);
      }
    }
#pragma unroll
    for (int c = 0; c < 2; c++) {
      const int row = 16 * w + r8 + 8 * c;
      const uint32_t addr = sbase + OFF_PHI + (qq >> 1) * 8192 + row * 128 + ((((qq & 1) * 4 + q) ^ (row & 7)) << 4);
      asm volatile("st.shared.v4.b32 [%0], {%1, %2, %3, %4};" ::"r"(addr), "r"(ore[c][0]), "r"(ore[c][1]), "r"(ore[c][2]), "r"(ore[c][3]) : "memory");
      asm volatile("st.shared.v4.b32 [%0], {%1, %2, %3, %4};" ::"r"(addr + 32768), "r"(oim[c][0]), "r"(oim[c][1]), "r"(oim[c][2]), "r"(oim[c][3]) : "memory");
    }
  }
  fence_async_smem();
  wg_bar(1 + cw);
  if ((threadIdx.x & 127) == 0) mbar_arrive(sbase + OFF_BAR + B_JOB + 8 * cw);
}

__device__ __forceinline__ void q_issue_num(float (&num)[20], const uint32_t (&pos)[8], const uint32_t (&neg)[8], uint32_t b) {
  wgmma_fence();
  wgmma_m64n40k16_rs_init<1>(num, pos[0], pos[1], pos[2], pos[3], make_desc(b, 640, 128, 0));
  wgmma_m64n40k16_rs<1>(num, pos[4], pos[5], pos[6], pos[7], make_desc(b + 1280, 640, 128, 0));
  wgmma_m64n40k16_rs<1>(num, neg[0], neg[1], neg[2], neg[3], make_desc(b + 2560, 640, 128, 0));
  wgmma_m64n40k16_rs<1>(num, neg[4], neg[5], neg[6], neg[7], make_desc(b + 3840, 640, 128, 0));
  wgmma_commit();
}
__device__ __forceinline__ void q_store_o(const float (&num)[20], uint32_t rowaddr, int chunk0) {
  const int lane = threadIdx.x & 31, mi = lane >> 3, rin = lane & 7;
  const float d0 = __shfl_sync(0xffffffffu, num[16], lane & ~3), d1 = __shfl_sync(0xffffffffu, num[18], lane & ~3);
  const float i0 = __fdividef(1.0f, d0 + 1e-6f), i1 = __fdividef(1.0f, d1 + 1e-6f);
#pragma unroll
  for (int jp = 0; jp < 2; jp++) {
    const int c0 = chunk0 + jp * 2 + (mi >> 1);
    stmatrix_x4(rowaddr + ((c0 ^ rin) << 4), pack_bf16(num[8 * jp] * i0, num[8 * jp + 1] * i0),
                pack_bf16(num[8 * jp + 2] * i1, num[8 * jp + 3] * i1), pack_bf16(num[8 * jp + 4] * i0, num[8 * jp + 5] * i0),
                pack_bf16(num[8 * jp + 6] * i1, num[8 * jp + 7] * i1));
  }
}
__device__ __forceinline__ void epi_attn(float (&acc0)[64], float (&acc1)[64], uint32_t sbase, int cw, bool isq) {
  const int t = threadIdx.x & 127, lane = t & 31, w = t >> 5, q = lane & 3, r8 = lane >> 2;
  const int mi = lane >> 3, rin = lane & 7;
  const int row0 = w * 16 + (mi & 1) * 8 + rin;
  uint32_t kf[2][16];
  if (isq) {
#pragma unroll
    for (int j = 0; j < 16; j += 2) {
      const uint32_t addr = sbase + OFF_PHI + (j >> 3) * 16384 + row0 * 128 + ((((j & 7) + (mi >> 1)) ^ rin) << 4);
      stmatrix_x4(addr, pack_bf16(acc0[4 * j], acc0[4 * j + 1]), pack_bf16(acc0[4 * j + 2], acc0[4 * j + 3]),
                  pack_bf16(acc0[4 * j + 4], acc0[4 * j + 5]), pack_bf16(acc0[4 * j + 6], acc0[4 * j + 7]));
      stmatrix_x4(addr + 8192, pack_bf16(acc1[4 * j], acc1[4 * j + 1]), pack_bf16(acc1[4 * j + 2], acc1[4 * j + 3]),
                  pack_bf16(acc1[4 * j + 4], acc1[4 * j + 5]), pack_bf16(acc1[4 * j + 6], acc1[4 * j + 7]));
    }
#pragma unroll
    for (int i = 0; i < 16; i++) { kf[0][i] = 0; kf[1][i] = 0; }
  } else {
#pragma unroll
    for (int j = 8; j < 16; j += 2) {
      const uint32_t addr = sbase + OFF_PHI + 16384 + ((j - 8) >> 2) * 8192 + row0 * 64 + ((((j & 3) + (mi >> 1)) ^ ((row0 >> 1) & 3)) << 4);
      stmatrix_x4(addr, pack_bf16(acc0[4 * j], acc0[4 * j + 1]), pack_bf16(acc0[4 * j + 2], acc0[4 * j + 3]),
                  pack_bf16(acc0[4 * j + 4], acc0[4 * j + 5]), pack_bf16(acc0[4 * j + 6], acc0[4 * j + 7]));
      stmatrix_x4(addr + 4096, pack_bf16(acc1[4 * j], acc1[4 * j + 1]), pack_bf16(acc1[4 * j + 2], acc1[4 * j + 3]),
                  pack_bf16(acc1[4 * j + 4], acc1[4 * j + 5]), pack_bf16(acc1[4 * j + 6], acc1[4 * j + 7]));
    }
#pragma unroll
    for (int i = 0; i < 16; i++) {
      kf[0][i] = pack_bf16(acc0[2 * i], acc0[2 * i + 1]);
      kf[1][i] = pack_bf16(acc1[2 * i], acc1[2 * i + 1]);
    }
  }
  fence_async_smem();
  wg_bar(1 + cw);
  const int nsub = isq ? 2 : 1;
#pragma unroll 1
  for (int sub = 0; sub < nsub; sub++) {
    const uint32_t tile = sbase + OFF_PHI + sub * 16384;
    const uint32_t wp = sbase + OFF_WPHI + (isq ? 2 * sub : 2 * cw) * 2048;
    float pq[4][16];
    uint32_t pos[4][8], neg[4][8];
    if (isq) {
      wgmma_fence();
#pragma unroll
      for (int i = 0; i < 4; i++) {
        const uint32_t a = tile + (i & 1) * 8192 + (i >> 1) * 64, b = wp + (i >> 1) * 2048;
        wgmma_m64n32k16_ss_init<0, 1>(pq[i], make_desc(a, 16, 1024, 1), make_desc(b, 512, 512, 2));
        wgmma_m64n32k16_ss<0, 1>(pq[i], make_desc(a + 32, 16, 1024, 1), make_desc(b + 1024, 512, 512, 2));
      }
    } else {
      wgmma_fence();
#pragma unroll
      for (int i = 0; i < 4; i++) {
        const uint32_t b = wp + (i >> 1) * 2048;
        const uint32_t* f = &kf[i & 1][8 * (i >> 1)];
        wgmma_m64n32k16_rs_init<1>(pq[i], f[0], f[1], f[2], f[3], make_desc(b, 512, 512, 2));
        wgmma_m64n32k16_rs<1>(pq[i], f[4], f[5], f[6], f[7], make_desc(b + 1024, 512, 512, 2));
      }
    }
    wgmma_commit();
    wgmma_wait<0>();
#pragma unroll
    for (int i = 0; i < 4; i++) fence_regs(pq[i]);
    dual_softmax_n<4>(pq, pos, neg);
    if (!isq) {
      float kvacc[2][20];
      mbar_wait(sbase + OFF_BAR + B_EBF + 8 + 8 * cw, 0);
#pragma unroll
      for (int hh = 0; hh < 2; hh++) {
#pragma unroll
        for (int half = 0; half < 2; half++) {
          const uint32_t rb = sbase + OFF_PHI + hh * 32768 + (half * 64 + row0) * 128;
#pragma unroll
          for (int jp = 0; jp < 2; jp++) {
            const int c0 = jp * 2 + (mi >> 1), i = 2 * hh + half;
            stmatrix_x4(rb + ((c0 ^ rin) << 4), pos[i][4 * jp], pos[i][4 * jp + 1], pos[i][4 * jp + 2], pos[i][4 * jp + 3]);
            stmatrix_x4(rb + (((c0 + 4) ^ rin) << 4), neg[i][4 * jp], neg[i][4 * jp + 1], neg[i][4 * jp + 2], neg[i][4 * jp + 3]);
          }
        }
      }
      fence_async_smem();
      wg_bar(1 + cw);
      wgmma_fence();
#pragma unroll
      for (int hh = 0; hh < 2; hh++)
#pragma unroll
        for (int ks = 0; ks < 8; ks++) {
          const uint32_t vb = sbase + OFF_PHI + 16384 + hh * 8192 + ks * 1024;
          const uint64_t da = make_desc(sbase + OFF_PHI + hh * 32768 + ks * 2048, 1024, 1024, 1);
          const uint64_t db = make_desc(vb, sbase + OFF_ONES - vb, 512, 2);
          if (ks == 0) wgmma_m64n40k16_ss_init<1, 1>(kvacc[hh], da, db);
          else wgmma_m64n40k16_ss<1, 1>(kvacc[hh], da, db);
        }
      wgmma_commit();
      wgmma_wait<0>();
      fence_regs(kvacc[0]);
      fence_regs(kvacc[1]);
      wg_bar(1 + cw);
      if (t == 0) mbar_arrive(sbase + OFF_BAR + B_EBA + 8 * cw);
#pragma unroll
      for (int hh = 0; hh < 2; hh++) {
#pragma unroll
        for (int rr = 0; rr < 2; rr++) {
          const int off = ((16 * w + r8 + 8 * rr) * KVW + 2 * q) * 4;
#pragma unroll
          for (int j = 0; j < 5; j++) {
            const int o = off + 32 * j;
            const uint32_t dst = (hh == 0) ? sbase + OFF_PHI + o
                                           : (o < 6144 ? sbase + OFF_PHI + 10240 + o : sbase + OFF_V + 16384 - 6144 + o);
            asm volatile("st.shared.v2.f32 [%0], {%1, %2};" ::"r"(dst), "f"(kvacc[hh][4 * j + 2 * rr]), "f"(kvacc[hh][4 * j + 2 * rr + 1]) : "memory");
          }
        }
      }
      fence_async_smem();
      wg_bar(1 + cw);
      if (t == 0) mbar_arrive(sbase + OFF_BAR + B_JOB + 16 + 8 * cw);
    } else {
      float num[4][20];
      mbar_wait(sbase + OFF_BAR + B_KVX + 8 * sub, 0);
#pragma unroll
      for (int i = 0; i < 4; i++) q_issue_num(num[i], pos[i], neg[i], sbase + OFF_V + (2 * sub + (i >> 1)) * 5120);
      wgmma_wait<2>();
      fence_regs(num[0]); fence_regs(num[1]);
      q_store_o(num[0], tile + row0 * 128, 0);
      q_store_o(num[1], tile + 8192 + row0 * 128, 0);
      wgmma_wait<0>();
      fence_regs(num[2]); fence_regs(num[3]);
      q_store_o(num[2], tile + row0 * 128, 4);
      q_store_o(num[3], tile + 8192 + row0 * 128, 4);
      fence_async_smem();
      wg_bar(1);
      if (t == 0) mbar_arrive(sbase + OFF_BAR + B_JOB + 32 + 8 * sub);
    }
  }
}

__device__ __forceinline__ void helper_kv(uint32_t sbase, int g, unsigned epoch) {
  const int h = threadIdx.x - 64;
  mbar_wait_long(sbase + OFF_BAR + B_EBA + 8, 0);
#pragma unroll 1
  for (int pr = 0; pr < 2; pr++) {
    if ((h & 31) == 0) {
      wait_ge(sbase + OFF_BAR, &g_flags.kvcnt[(g + 8 * pr) * 8], 16u * epoch);
    }
    __syncwarp();
    const float4* src = reinterpret_cast<const float4*>(g_kv + (size_t)(2 * g + 16 * pr) * 64 * KVW);
#pragma unroll 1
    for (int ib = 0; ib < 3; ib++) {
      float4 u[7];
#pragma unroll
      for (int i = 0; i < 7; i++) u[i] = __ldcg(src + min((ib * 7 + i) * 64 + h, 1279));
#pragma unroll
      for (int i = 0; i < 7; i++) {
        const int idx = min((ib * 7 + i) * 64 + h, 1279);
        const int f2 = idx / 10, j = idx - f2 * 10;
        const uint32_t dst = sbase + OFF_V + pr * 10240 + (f2 >> 3) * 640 + (j >> 1) * 128 + (f2 & 7) * 16 + (j & 1) * 8;
        asm volatile("st.shared.v2.b32 [%0], {%1, %2};" ::"r"(dst), "r"(pack_bf16(u[i].x, u[i].y)), "r"(pack_bf16(u[i].z, u[i].w)) : "memory");
      }
    }
    fence_async_smem();
    __syncwarp();
    if ((h & 31) == 0) mbar_arrive(sbase + OFF_BAR + B_KVX + 8 * pr);
  }
}

__device__ __forceinline__ void store_agent(const Params& prm, uint32_t sbase, int g, int rb, unsigned epoch) {
  const uint32_t bars = sbase + OFF_BAR;
  wait_ge(bars, &g_flags.zero_cnt, 128u * epoch);
  fence_async_global();
#pragma unroll 1
  for (int j = 0; j < 6; j++) {
    mbar_wait_long(bars + B_JOB + 8 * j, 0);
    unsigned* flag;
    if (j < 2) {
      const int G = g + 8 * j;
#pragma unroll 1
      for (int u = 0; u < 16; u++) {
        tma_store_3d(&prm.tmHTs, sbase + OFF_PHI + (u & 7) * 2048 + (u >> 3) * 32768, 0, (u >> 3) * 1024 + 64 * G + (u & 3) * 16, 2 * rb + ((u >> 2) & 1));
        __nanosleep(50);
      }
      flag = &g_flags.hcnt[rb * 8];
    } else if (j < 4) {
      const int hp = g + 8 * (j - 2);
#pragma unroll 1
      for (int u = 0; u < 10; u++) {
        const uint32_t o = u * 2048;
        const uint32_t src = (o < 16384) ? sbase + OFF_PHI + o : sbase + OFF_V + o;
        bulk_reduce_f32(g_kv + (size_t)(2 * hp) * 64 * KVW + o / 4, src, 2048);
        if (j == 2) __nanosleep(50);
      }
      flag = &g_flags.kvcnt[hp * 8];
    } else {
      tma_store_2d(&prm.tmO, sbase + OFF_PHI + (j - 4) * 16384, 64 * (g + 8 * (j - 4)), 128 * rb);
      flag = &g_flags.ocnt[(2 * rb + (j - 4)) * 8];
    }
    bulk_commit();
    if (j != 4) {
      bulk_wait_read();
      mbar_arrive(bars + B_EBF + 8 * (j < 4 ? j : 4));
    }
    bulk_wait_all();
    red_relaxed_add(flag, 1);
  }
}

constexpr int OST = 544;
__device__ __forceinline__ void stage_half(const float (&a)[64], uint32_t wbuf) {
  const int lane = threadIdx.x & 31, q = lane & 3, r8 = lane >> 2;
#pragma unroll
  for (int j = 0; j < 16; j++) {
    asm volatile("st.shared.v2.f32 [%0], {%1, %2};" ::"r"(wbuf + r8 * OST + j * 32 + q * 8), "f"(a[4 * j]), "f"(a[4 * j + 1]) : "memory");
    asm volatile("st.shared.v2.f32 [%0], {%1, %2};" ::"r"(wbuf + (r8 + 8) * OST + j * 32 + q * 8), "f"(a[4 * j + 2]), "f"(a[4 * j + 3]) : "memory");
  }
  __syncwarp();
}
__device__ __forceinline__ void store_y(float (&acc0)[64], const float (&acc1)[64], uint32_t wbuf, const Params& prm, int rb, int g) {
  const int lane = threadIdx.x & 31, w = (threadIdx.x & 127) >> 5;
  const uint2 dk = __ldg(reinterpret_cast<const uint2*>(prm.dskip + 128 * g) + lane);
#pragma unroll 1
  for (int half = 0; half < 2; half++) {
    const int m0 = 64 * half + 16 * w;
    const int t0 = rb * 128 + 32 * ((m0 >> 3) & 3) + 8 * (m0 >> 5);
    uint2 xs[16];
#pragma unroll
    for (int r = 0; r < 16; r++)
      xs[r] = __ldg(reinterpret_cast<const uint2*>(prm.xB + (size_t)(t0 + (r & 7) + (r >> 3) * 32) * DM + 128 * g) + lane);
    stage_half(acc0, wbuf);
    float* dst = prm.out + (size_t)t0 * 2048 + 1024 + 128 * g + 4 * lane;
#pragma unroll
    for (int r = 0; r < 16; r++) {
      float4 v = lds128(wbuf + r * OST + lane * 16);
      const float2 s0 = __bfloat1622float2(__hmul2(*reinterpret_cast<const __nv_bfloat162*>(&xs[r].x), *reinterpret_cast<const __nv_bfloat162*>(&dk.x)));
      const float2 s1 = __bfloat1622float2(__hmul2(*reinterpret_cast<const __nv_bfloat162*>(&xs[r].y), *reinterpret_cast<const __nv_bfloat162*>(&dk.y)));
      v.x += s0.x; v.y += s0.y; v.z += s1.x; v.w += s1.y;
      __stcs(reinterpret_cast<float4*>(dst + (size_t)((r & 7) + (r >> 3) * 32) * 2048), v);
    }
    __syncwarp();
#pragma unroll
    for (int i = 0; i < 64; i++) acc0[i] = acc1[i];
  }
}
__device__ __forceinline__ void drain_out(uint32_t wbuf, float* dst  ) {
  const int lane = threadIdx.x & 31;
#pragma unroll
  for (int r = 0; r < 16; r++) {
    const float4 v = lds128(wbuf + r * OST + lane * 16);
    const uint32_t p0 = pack_bf16(v.x, v.y), p1 = pack_bf16(v.z, v.w);
    __stcs(reinterpret_cast<float4*>(dst + (size_t)r * 2048) + lane,
           make_float4(__uint_as_float(p0 << 16), __uint_as_float(p0 & 0xffff0000u), __uint_as_float(p1 << 16), __uint_as_float(p1 & 0xffff0000u)));
  }
}

__global__ void __launch_bounds__(384, 1) fused_kernel(const __grid_constant__ Params prm) {
  extern __shared__ uint8_t smem_raw[];
  const uint32_t sbase = (smem_u32(smem_raw) + 1023) & ~1023u;
  const uint32_t bars = sbase + OFF_BAR;
  const int tid = threadIdx.x, wg = __shfl_sync(0xffffffffu, tid >> 7, 0);
  const int cl = blockIdx.x >> 1, rank = blockIdx.x & 1;
  const int g = cl >> 3, rb = 2 * (cl & 7) + rank;

  if (tid == 0) {
    for (int s = 0; s < STAGES; s++) { mbar_init(bars + 8 * s, 1);
      mbar_init(bars + B_EMPTY + 8 * s, 8);
    }
    mbar_init(bars + B_ORD, 1); mbar_init(bars + B_ORD + 8, 1); mbar_init(bars + B_WPHI, 1); mbar_init(bars + B_EPOCH, 1); mbar_init(bars + B_KVX, 2); mbar_init(bars + B_KVX + 8, 2);
    for (int j = 0; j < 6; j++) mbar_init(bars + B_JOB + 8 * j, 1);
    mbar_init(bars + B_PARAM, 2); mbar_init(bars + B_EBA, 1); mbar_init(bars + B_EBA + 8, 1);
    for (int j = 0; j < 5; j++) mbar_init(bars + B_EBF + 8 * j, 1);
    asm volatile("st.shared.u32 [%0], %1;" ::"r"(bars + B_DEAD), "r"(0u) : "memory");
    asm volatile("fence.mbarrier_init.release.cluster;" ::: "memory");
    asm volatile("fence.proxy.async.shared::cta;" ::: "memory");
#pragma unroll 1
    for (int kb = 0; kb < STAGES; kb++) {
      const uint32_t full = bars + 8 * kb, sw = sbase + kb * STAGE_BYTES;
      mbar_expect_tx(full, STAGE_BYTES);
      tma_5d(sw + 16384, &prm.tmXB, kb * 64, 0, 0, 0, rb, full);
      tma_2d(sw, &prm.tmBre, kb * 64, 64 * g, full);
      tma_2d(sw + 8192, &prm.tmBim, kb * 64, 64 * g, full);
    }
  } else if (tid == 32) {
    prefetch_tm(&prm.tmXB); prefetch_tm(rank ? &prm.tmBim : &prm.tmBre); prefetch_tm(&prm.tmWphi);
    prefetch_tm(&prm.tmXA); prefetch_tm(&prm.tmWqkv); prefetch_tm(&prm.tmHT);
    prefetch_tm(&prm.tmCre); prefetch_tm(&prm.tmCim); prefetch_tm(&prm.tmO); prefetch_tm(&prm.tmWo);
  } else if (tid >= 64 && tid < 128) {
    asm volatile("st.shared.v4.b32 [%0], {%1, %2, %2, %2};" ::"r"(sbase + OFF_ONES + (tid - 64) * 16), "r"(0x00003F80u), "r"(0u) : "memory");
    fence_async_smem();
  }
  __syncthreads();
  asm volatile("barrier.cluster.arrive.relaxed.aligned;\nbarrier.cluster.wait.acquire.aligned;" ::: "memory");

  if (wg == 0) {
    reg_dealloc<56>();
    const int warp = __shfl_sync(0xffffffffu, tid >> 5, 0), lane = tid & 31;
    if (warp == 0) {
      const bool leader = elect_one();
      if (leader) {
        mbar_expect_tx(bars + B_WPHI, 8192);
        tma_2d(sbase + OFF_WPHI, &prm.tmWphi, 0, 64 * g, bars + B_WPHI);
        tma_2d(sbase + OFF_WPHI + 4096, &prm.tmWphi, 0, 64 * g + 512, bars + B_WPHI);
      }
      int stage = 0;
      uint32_t phase = 0;
      unsigned epoch = 0;
      auto run = [&](auto kind, const CUtensorMap* tw, int w0, const CUtensorMap* tx, int kb0, int kb1) {
        constexpr int KIND = decltype(kind)::value;
#pragma unroll 1
        for (int kb = kb0; kb < kb1; kb++) {
          mbar_wait(bars + B_EMPTY + 8 * stage, phase);

          if (leader) {
            const uint32_t full = bars + 8 * stage;
            const uint32_t sw = sbase + stage * STAGE_BYTES;
            mbar_expect_tx(full, STAGE_BYTES);
            if (KIND == 0) {
              tma_2d_mc(sw + rank * 8192, tw, kb * 64, w0, full);
              tma_5d(sw + 16384, tx, kb * 64, 0, 0, 0, rb, full);
            } else if (KIND == 1) {
              tma_2d_mc(sw + rank * 8192, tw, w0, kb * 64, full);
              tma_2d(sw + 16384, tx, kb * 64, rb * 128, full);
            } else {
              tma_2d_mc(sw + rank * 8192, tw, (kb & 15) * 64, w0, full);
              tma_3d(sw + 16384, tx, 0, kb * 64, 2 * rb, full);
            }
          }
          if (++stage == STAGES) { stage = 0; phase ^= 1; }
        }
      };
      using K0 = std::integral_constant<int, 0>;
      using K1 = std::integral_constant<int, 1>;
      using K2 = std::integral_constant<int, 2>;
#pragma unroll 1
      for (int i = 0; i < 2; i++) run(K0{}, rank ? &prm.tmBim : &prm.tmBre, 64 * (g + 8 * i), &prm.tmXB, i == 0 ? STAGES : 0, 16);
#pragma unroll 1
      for (int i = 0; i < 3; i++)
        run(K1{}, &prm.tmWqkv, i < 2 ? 1024 + rank * 1024 + 64 * (g + 8 * i) : 64 * (g + 8 * rank), &prm.tmXA, 0, 16);
      mbar_wait(bars + B_EPOCH, 0);
      asm volatile("ld.shared.u32 %0, [%1];" : "=r"(epoch) : "r"(bars + B_EPOCHV) : "memory");
      wait_ge(bars, &g_flags.hcnt[rb * 8], 16u * epoch);
      fence_async_global();
#pragma unroll 1
      for (int i = 0; i < 2; i++) run(K2{}, i ? &prm.tmCim : &prm.tmCre, 128 * g + 64 * rank, &prm.tmHT, 16 * i, 16 * i + 16);
#pragma unroll 1
      for (int i = 0; i < 2; i++) {
        wait_ge(bars, &g_flags.ocnt[(2 * rb + i) * 8], 8u * epoch);
        fence_async_global();
        run(K1{}, &prm.tmWo, 128 * g + 64 * rank, &prm.tmO, 8 * i, 8 * i + 8);
      }
    } else if (warp == 1) {
      unsigned epoch = 0;
      if (lane == 0) {
        epoch = (atomicAdd(&g_flags.ticket, 1u) >> 7) + 1u;
        asm volatile("st.shared.u32 [%0], %1;" ::"r"(bars + B_EPOCHV), "r"(epoch) : "memory");
        mbar_arrive(bars + B_EPOCH);
      }
      uint4* z = reinterpret_cast<uint4*>(g_kv) + blockIdx.x * 160;
#pragma unroll
      for (int i = 0; i < 5; i++) __stcg(z + i * 32 + lane, make_uint4(0, 0, 0, 0));
      __syncwarp();
      if (lane == 0) {
        red_release_add(&g_flags.zero_cnt, 1);
        store_agent(prm, sbase, g, rb, epoch);
      }
    } else {
#pragma unroll 1
      for (int c = 0; c < 2; c++) {
        const int ch = tid - 64, p = 64 * (g + 8 * c) + ch;
        chan_params(__bfloat162float(prm.lam_re[p]), __bfloat162float(prm.lam_im[p]), __bfloat162float(prm.log_dt[p]),
                    sbase + OFF_PHI + 16384 + (c * 64 + ch) * PSTRIDE);
      }
      __syncwarp();
      if (lane == 0) mbar_arrive(bars + B_PARAM);
      unsigned epoch;
      mbar_wait(bars + B_EPOCH, 0);
      asm volatile("ld.shared.u32 %0, [%1];" : "=r"(epoch) : "r"(bars + B_EPOCHV) : "memory");
      helper_kv(sbase, g, epoch);
    }
    __syncwarp();
    asm volatile("barrier.cluster.arrive.relaxed.aligned;\nbarrier.cluster.wait.aligned;" ::: "memory");
  } else {
    reg_alloc<224>();
    const int cw = wg - 1;
    const int t = tid & 127, lane = t & 31, w = t >> 5, r8 = lane >> 2;
    float acc0[64], acc1[64];
    unsigned epoch;
    {
      const int G = g + 8 * cw;
      ChanParams cp[2];
      const uint32_t ptab = sbase + OFF_PHI + 16384 + (cw * 64 + 16 * w + r8) * PSTRIDE;
      if (cw == 1) {
        mbar_wait(bars + B_PARAM, 0);
#pragma unroll
        for (int c = 0; c < 2; c++) cp[c] = load_params(ptab + 8 * c * PSTRIDE, lane & 3);
      }
      mainloop<0>(acc0, acc1, 16 * cw, 16, sbase, cw, cw ^ 1);
      if (cw == 0) {
        mbar_wait(bars + B_PARAM, 0);
#pragma unroll
        for (int c = 0; c < 2; c++) cp[c] = load_params(ptab + 8 * c * PSTRIDE, lane & 3);
      }
      mbar_wait(bars + B_EPOCH, 0);
      asm volatile("ld.shared.u32 %0, [%1];" : "=r"(epoch) : "r"(bars + B_EPOCHV) : "memory");
      epi_bu(acc0, acc1, cp, sbase, G, rb, cw, epoch);
    }
#pragma unroll 1
    for (int step = 0; step < 3; step++) {
      const int it0 = cw ? 48 : (step == 0 ? 32 : (step == 1 ? 64 : 112));
      mainloop<1>(acc0, acc1, it0, 16, sbase, cw, cw ? 1 : (step & 1));
      if (step == 2) {
        stage_half(acc1, sbase + (4 + w) * 16 * OST);
        asm volatile("bar.arrive 3, 256;" ::: "memory");
        stage_half(acc0, sbase + w * 16 * OST);
        drain_out(sbase + w * 16 * OST, prm.out + (size_t)(rb * 128 + 16 * w) * 2048 + 128 * g);
        break;
      }
      mbar_wait(bars + B_WPHI, 0);
      if (cw == 1) {
        mbar_wait(bars + B_EBA, 0);
      } else if (step == 1) {
        mbar_wait(bars + B_EBA + 8, 0);
        mbar_wait(bars + B_EBF + 24, 0);
      }
      epi_attn(acc0, acc1, sbase, cw, step == 1);
      if (cw == 1) break;
    }
    if (cw == 1) {
      mainloop<2>(acc0, acc1, 80, 32, sbase, 1, 0);
      mbar_wait(bars + B_EBF + 32, 0);
      store_y(acc0, acc1, sbase + OFF_EB + w * 16 * OST, prm, rb, g);
      asm volatile("bar.sync 3, 256;" ::: "memory");
      drain_out(sbase + (4 + w) * 16 * OST, prm.out + (size_t)(rb * 128 + 64 + 16 * w) * 2048 + 128 * g);
    }
    asm volatile("barrier.cluster.arrive.relaxed.aligned;\nbarrier.cluster.wait.aligned;" ::: "memory");
  }
}

typedef CUresult (*PFN_encodeTiled)(CUtensorMap*, CUtensorMapDataType, cuuint32_t, void*, const cuuint64_t*, const cuuint64_t*,
                                    const cuuint32_t*, const cuuint32_t*, CUtensorMapInterleave, CUtensorMapSwizzle,
                                    CUtensorMapL2promotion, CUtensorMapFloatOOBfill);

bool make_tm(PFN_encodeTiled enc, CUtensorMap* tm, const void* base, int rank, const uint64_t* dims, const uint64_t* strides,
             const uint32_t* box, CUtensorMapSwizzle sw) {
  cuuint64_t gd[5], gs[5];
  cuuint32_t bx[5], es[5];
  for (int i = 0; i < rank; i++) { gd[i] = dims[i]; bx[i] = box[i]; es[i] = 1; }
  for (int i = 0; i + 1 < rank; i++) gs[i] = strides[i];
  return enc(tm, CU_TENSOR_MAP_DATA_TYPE_BFLOAT16, rank, const_cast<void*>(base), gd, gs, bx, es, CU_TENSOR_MAP_INTERLEAVE_NONE, sw,
             CU_TENSOR_MAP_L2_PROMOTION_L2_256B, CU_TENSOR_MAP_FLOAT_OOB_FILL_NONE) == CUDA_SUCCESS;
}
bool make_tm2(PFN_encodeTiled enc, CUtensorMap* tm, const void* base, uint64_t inner, uint64_t outer, uint32_t b0, uint32_t b1,
              CUtensorMapSwizzle sw = CU_TENSOR_MAP_SWIZZLE_128B) {
  const uint64_t dims[2] = {inner, outer}, str[1] = {inner * 2};
  const uint32_t box[2] = {b0, b1};
  return make_tm(enc, tm, base, 2, dims, str, box, sw);
}

}

extern "C" void kernel_launch(void* const* d_in, const int* in_sizes, int n_in, void* d_out, int out_size) {
  (void)in_sizes; (void)n_in; (void)out_size;
  static PFN_encodeTiled enc = nullptr;
  static void *pHT = nullptr, *pO = nullptr;
  if (!enc) {
    void* fn = nullptr;
    cudaDriverEntryPointQueryResult qr;
    if (cudaGetDriverEntryPoint("cuTensorMapEncodeTiled", &fn, cudaEnableDefault, &qr) != cudaSuccess || !fn) return;
    enc = (PFN_encodeTiled)fn;
    cudaFuncSetAttribute(fused_kernel, cudaFuncAttributeMaxDynamicSharedMemorySize, SMEM_BYTES);
    cudaGetSymbolAddress(&pHT, g_HT);
    cudaGetSymbolAddress(&pO, g_O);
  }
  Params prm;
  bool ok = true;
  {
    const uint64_t dims[5] = {1024, 2, 4, 16, 16}, str[4] = {2048, 65536, 4096, 262144};
    const uint32_t box[5] = {64, 2, 4, 16, 1};
    ok &= make_tm(enc, &prm.tmXB, d_in[4], 5, dims, str, box, CU_TENSOR_MAP_SWIZZLE_128B);
  }
  ok &= make_tm2(enc, &prm.tmBre, d_in[7], 1024, 1024, 64, 64);
  ok &= make_tm2(enc, &prm.tmBim, d_in[8], 1024, 1024, 64, 64);
  ok &= make_tm2(enc, &prm.tmXA, d_in[0], 1024, 2048, 64, 128);
  ok &= make_tm2(enc, &prm.tmWqkv, d_in[1], 3072, 1024, 64, 64);
  ok &= make_tm2(enc, &prm.tmWphi, d_in[2], 32, 1024, 32, 64, CU_TENSOR_MAP_SWIZZLE_64B);
  {
    const uint64_t dims[3] = {64, 2048, 32}, str[2] = {4096, 128};
    const uint32_t box[3] = {64, 64, 2};
    ok &= make_tm(enc, &prm.tmHT, pHT, 3, dims, str, box, CU_TENSOR_MAP_SWIZZLE_128B);
  }
  {
    const uint64_t dims[3] = {64, 2048, 32}, str[2] = {4096, 128};
    const uint32_t box[3] = {64, 16, 1};
    ok &= make_tm(enc, &prm.tmHTs, pHT, 3, dims, str, box, CU_TENSOR_MAP_SWIZZLE_128B);
  }
  ok &= make_tm2(enc, &prm.tmCre, d_in[9], 1024, 1024, 64, 64);
  ok &= make_tm2(enc, &prm.tmCim, d_in[10], 1024, 1024, 64, 64);
  ok &= make_tm2(enc, &prm.tmO, pO, 1024, 2048, 64, 128);
  ok &= make_tm2(enc, &prm.tmWo, d_in[3], 1024, 1024, 64, 64);
  if (!ok) return;
  prm.xB = (const __nv_bfloat16*)d_in[4];
  prm.lam_re = (const __nv_bfloat16*)d_in[5];
  prm.lam_im = (const __nv_bfloat16*)d_in[6];
  prm.log_dt = (const __nv_bfloat16*)d_in[11];
  prm.dskip = (const __nv_bfloat16*)d_in[12];
  prm.out = (float*)d_out;

  cudaLaunchConfig_t cfg = {};
  cfg.gridDim = dim3(128);
  cfg.blockDim = dim3(384);
  cfg.dynamicSmemBytes = SMEM_BYTES;
  cfg.stream = cudaStreamPerThread;
  cudaLaunchAttribute attr[1];
  attr[0].id = cudaLaunchAttributeClusterDimension;
  attr[0].val.clusterDim.x = 2; attr[0].val.clusterDim.y = 1; attr[0].val.clusterDim.z = 1;
  cfg.attrs = attr;
  cfg.numAttrs = 1;
  cudaLaunchKernelEx(&cfg, fused_kernel, prm);
}
```

```cpp
#include <cuda_runtime.h>
#include <cuda_bf16.h>
#include <cuda.h>
#include <stdint.h>
#include <type_traits>

namespace {

constexpr int SEQ = 2048;
constexpr int DM = 1024;
constexpr int STAGES = 5;
constexpr int STAGE_BYTES = 32768;
constexpr int OFF_EB = STAGES * STAGE_BYTES;
constexpr int OFF_PHI = OFF_EB;
constexpr int OFF_V = OFF_EB + 32768;
constexpr int OFF_WPHI = OFF_EB + 53248;
constexpr int OFF_ONES = OFF_EB + 61440;
constexpr int OFF_BAR = OFF_EB + 62464;
constexpr int SMEM_BYTES = OFF_BAR + 512 + 1024;
constexpr int B_EMPTY = 64, B_ORD = 128  , B_WPHI = 144, B_EPOCH = 152, B_PARAM = 160, B_KVX = 168  , B_EBA = 184  ,
              B_EPOCHV = 200, B_DEAD = 204, B_JOB = 208  , B_EBF = 256  ;

constexpr int KVW = 40;

struct Params {
  CUtensorMap tmXB;
  CUtensorMap tmBre, tmBim;
  CUtensorMap tmXA;
  CUtensorMap tmWqkv;
  CUtensorMap tmWphi;
  CUtensorMap tmHT;
  CUtensorMap tmHTs;
  CUtensorMap tmCre, tmCim;
  CUtensorMap tmO;
  CUtensorMap tmWo;
  const __nv_bfloat16* xB;
  const __nv_bfloat16* lam_re;
  const __nv_bfloat16* lam_im;
  const __nv_bfloat16* log_dt;
  const __nv_bfloat16* dskip;
  float* out;
};

__device__ __nv_bfloat16 g_HT[2048 * 2048];
__device__ __nv_bfloat16 g_O[SEQ * DM];
__device__ float g_kv[32 * 64 * KVW];
__device__ uint4 g_E[16 * 16 * 64];
struct Flags {
  unsigned ticket;   unsigned pad0[31];
  unsigned zero_cnt; unsigned pad1[31];
  unsigned hcnt[16 * 8];
  unsigned kvcnt[16 * 8];
  unsigned ocnt[2 * 16 * 8];
};
__device__ Flags g_flags;

__device__ __forceinline__ uint32_t smem_u32(const void* p) { return (uint32_t)__cvta_generic_to_shared(p); }
__device__ __forceinline__ void mbar_init(uint32_t bar, uint32_t count) {
  asm volatile("mbarrier.init.shared::cta.b64 [%0], %1;" ::"r"(bar), "r"(count));
}
__device__ __forceinline__ void mbar_expect_tx(uint32_t bar, uint32_t bytes) {
  asm volatile("mbarrier.arrive.expect_tx.shared::cta.b64 _, [%0], %1;" ::"r"(bar), "r"(bytes) : "memory");
}
__device__ __forceinline__ void mbar_arrive(uint32_t bar) {
  asm volatile("mbarrier.arrive.shared::cta.b64 _, [%0];" ::"r"(bar) : "memory");
}
__device__ __forceinline__ void mbar_arrive_cluster(uint32_t bar, uint32_t cta) {
  asm volatile("{\n.reg .b32 ra;\nmapa.shared::cluster.u32 ra, %0, %1;\nmbarrier.arrive.shared::cluster.b64 _, [ra];\n}" ::"r"(bar), "r"(cta) : "memory");
}
__device__ __forceinline__ uint32_t dead_addr(uint32_t bar) { return (bar & ~0x1FFu) + B_DEAD; }
__device__ __forceinline__ void mbar_wait(uint32_t bar, uint32_t parity) {
  asm volatile(
      "{\n.reg .pred p;\n.reg .u32 c, d;\n"
      "mov.u32 c, 0;\n"
      "WAIT_LOOP:\n"
      "mbarrier.try_wait.parity.shared::cta.b64 p, [%0], %1;\n"
      "@p bra WAIT_DONE;\n"
      "add.u32 c, c, 1;\n"
      "setp.gt.u32 p, c, 0x200000;\n"
      "@p st.volatile.shared.u32 [%2], c;\n"
      "ld.volatile.shared.u32 d, [%2];\n"
      "setp.eq.u32 p, d, 0;\n"
      "@p bra WAIT_LOOP;\n"
      "WAIT_DONE:\n}\n" ::"r"(bar), "r"(parity), "r"(dead_addr(bar)) : "memory");
}
__device__ __forceinline__ void mbar_wait_long(uint32_t bar, uint32_t parity) {
  asm volatile(
      "{\n.reg .pred p;\n.reg .u32 c, d;\n"
      "mov.u32 c, 0;\n"
      "WAITL_LOOP:\n"
      "mbarrier.try_wait.parity.shared::cta.b64 p, [%0], %1;\n"
      "@p bra WAITL_DONE;\n"
      "nanosleep.u32 100;\n"
      "add.u32 c, c, 1;\n"
      "setp.gt.u32 p, c, 0x200000;\n"
      "@p st.volatile.shared.u32 [%2], c;\n"
      "ld.volatile.shared.u32 d, [%2];\n"
      "setp.eq.u32 p, d, 0;\n"
      "@p bra WAITL_LOOP;\n"
      "WAITL_DONE:\n}\n" ::"r"(bar), "r"(parity), "r"(dead_addr(bar)) : "memory");
}
__device__ __forceinline__ bool give_up(uint32_t bars, unsigned spins) {
  unsigned d;
  if (spins > (1u << 20)) asm volatile("st.volatile.shared.u32 [%0], %1;" ::"r"(bars + B_DEAD), "r"(spins) : "memory");
  asm volatile("ld.volatile.shared.u32 %0, [%1];" : "=r"(d) : "r"(bars + B_DEAD) : "memory");
  return d != 0;
}
__device__ __forceinline__ unsigned ld_relaxed(const unsigned* p) {
  unsigned v;
  asm volatile("ld.relaxed.gpu.global.u32 %0, [%1];" : "=r"(v) : "l"(p) : "memory");
  return v;
}
__device__ __forceinline__ void wait_ge(uint32_t bars, const unsigned* p, unsigned target) {
  unsigned spins = 0;
  while ((int)(ld_relaxed(p) - target) < 0) {
    __nanosleep(128);
    if (give_up(bars, ++spins)) break;
  }
  asm volatile("{\n.reg .u32 v;\nld.acquire.gpu.global.u32 v, [%0];\n}" ::"l"(p) : "memory");
}
__device__ __forceinline__ void red_release_add(unsigned* p, unsigned v) {
  asm volatile("red.release.gpu.global.add.u32 [%0], %1;" ::"l"(p), "r"(v) : "memory");
}
__device__ __forceinline__ void red_relaxed_add(unsigned* p, unsigned v) {
  asm volatile("red.relaxed.gpu.global.add.u32 [%0], %1;" ::"l"(p), "r"(v) : "memory");
}
__device__ __forceinline__ void st_tagged(uint4* p, float a, float b, unsigned tag) {
  const unsigned long long w0 = ((unsigned long long)tag << 32) | __float_as_uint(a);
  const unsigned long long w1 = ((unsigned long long)tag << 32) | __float_as_uint(b);
  asm volatile("st.relaxed.gpu.global.v2.b64 [%0], {%1, %2};" ::"l"(p), "l"(w0), "l"(w1) : "memory");
}
__device__ __forceinline__ void bulk_commit() { asm volatile("cp.async.bulk.commit_group;" ::: "memory"); }
__device__ __forceinline__ void bulk_wait_read() { asm volatile("cp.async.bulk.wait_group.read 0;" ::: "memory"); }
__device__ __forceinline__ void bulk_wait_all() { asm volatile("cp.async.bulk.wait_group 0;" ::: "memory"); }
__device__ __forceinline__ void bulk_reduce_f32(float* dst, uint32_t src, uint32_t bytes) {
  asm volatile("cp.reduce.async.bulk.global.shared::cta.bulk_group.add.f32 [%0], [%1], %2;" ::"l"(dst), "r"(src), "r"(bytes) : "memory");
}
__device__ __forceinline__ void tma_store_3d(const CUtensorMap* tm, uint32_t src, int c0, int c1, int c2) {
  asm volatile("cp.async.bulk.tensor.3d.global.shared::cta.bulk_group [%0, {%2, %3, %4}], [%1];"
               ::"l"(tm), "r"(src), "r"(c0), "r"(c1), "r"(c2) : "memory");
}
__device__ __forceinline__ void fence_async_global() { asm volatile("fence.proxy.async.global;" ::: "memory"); }
__device__ __forceinline__ void fence_async_smem() { asm volatile("fence.proxy.async.shared::cta;" ::: "memory"); }
__device__ __forceinline__ void tma_2d(uint32_t dst, const CUtensorMap* tm, int c0, int c1, uint32_t bar) {
  asm volatile("cp.async.bulk.tensor.2d.shared::cluster.global.mbarrier::complete_tx::bytes [%0], [%1, {%3, %4}], [%2];"
               ::"r"(dst), "l"(tm), "r"(bar), "r"(c0), "r"(c1) : "memory");
}
__device__ __forceinline__ void tma_3d(uint32_t dst, const CUtensorMap* tm, int c0, int c1, int c2, uint32_t bar) {
  asm volatile("cp.async.bulk.tensor.3d.shared::cluster.global.mbarrier::complete_tx::bytes [%0], [%1, {%3, %4, %5}], [%2];"
               ::"r"(dst), "l"(tm), "r"(bar), "r"(c0), "r"(c1), "r"(c2) : "memory");
}
__device__ __forceinline__ void tma_5d(uint32_t dst, const CUtensorMap* tm, int c0, int c1, int c2, int c3, int c4, uint32_t bar) {
  asm volatile("cp.async.bulk.tensor.5d.shared::cluster.global.mbarrier::complete_tx::bytes [%0], [%1, {%3, %4, %5, %6, %7}], [%2];"
               ::"r"(dst), "l"(tm), "r"(bar), "r"(c0), "r"(c1), "r"(c2), "r"(c3), "r"(c4) : "memory");
}
__device__ __forceinline__ void tma_2d_mc(uint32_t dst, const CUtensorMap* tm, int c0, int c1, uint32_t bar) {
  asm volatile("cp.async.bulk.tensor.2d.shared::cluster.global.mbarrier::complete_tx::bytes.multicast::cluster [%0], [%1, {%3, %4}], [%2], %5;"
               ::"r"(dst), "l"(tm), "r"(bar), "r"(c0), "r"(c1), "h"((uint16_t)3) : "memory");
}
__device__ __forceinline__ void tma_store_2d(const CUtensorMap* tm, uint32_t src, int c0, int c1) {
  asm volatile("cp.async.bulk.tensor.2d.global.shared::cta.bulk_group [%0, {%2, %3}], [%1];"
               ::"l"(tm), "r"(src), "r"(c0), "r"(c1) : "memory");
}
__device__ __forceinline__ bool elect_one() {
  uint32_t p;
  asm volatile("{\n.reg .pred e;\nelect.sync _|e, 0xffffffff;\nselp.u32 %0, 1, 0, e;\n}" : "=r"(p));
  return p != 0;
}
__device__ __forceinline__ void prefetch_tm(const CUtensorMap* tm) {
  asm volatile("prefetch.tensormap [%0];" ::"l"(tm) : "memory");
}
__device__ __forceinline__ void wgmma_fence() { asm volatile("wgmma.fence.sync.aligned;" ::: "memory"); }
__device__ __forceinline__ void wgmma_commit() { asm volatile("wgmma.commit_group.sync.aligned;" ::: "memory"); }
template <int N> __device__ __forceinline__ void wgmma_wait() { asm volatile("wgmma.wait_group.sync.aligned %0;" ::"n"(N) : "memory"); }
__device__ __forceinline__ void wg_bar(int id) {
  if (id == 1) asm volatile("bar.sync 1, 128;" ::: "memory");
  else asm volatile("bar.sync 2, 128;" ::: "memory");
}
template <int R> __device__ __forceinline__ void reg_alloc() { asm volatile("setmaxnreg.inc.sync.aligned.u32 %0;" ::"n"(R)); }
template <int R> __device__ __forceinline__ void reg_dealloc() { asm volatile("setmaxnreg.dec.sync.aligned.u32 %0;" ::"n"(R)); }

__device__ __forceinline__ uint64_t make_desc(uint32_t saddr, uint32_t lbo_bytes, uint32_t sbo_bytes, uint32_t layout) {
  uint64_t d = (uint64_t)((saddr & 0x3FFFF) >> 4);
  d |= (uint64_t)((lbo_bytes & 0x3FFFF) >> 4) << 16;
  d |= (uint64_t)((sbo_bytes & 0x3FFFF) >> 4) << 32;
  d |= (uint64_t)layout << 62;
  return d;
}
__device__ __forceinline__ uint64_t desc128(uint32_t lo) { return ((uint64_t)0x40000040u << 32) | lo; }
__device__ __forceinline__ uint32_t pack_bf16(float lo, float hi) {
  uint32_t r;
  asm("cvt.rn.bf16x2.f32 %0, %1, %2;" : "=r"(r) : "f"(hi), "f"(lo));
  return r;
}
__device__ __forceinline__ float ex2(float x) { float y; asm("ex2.approx.ftz.f32 %0, %1;" : "=f"(y) : "f"(x)); return y; }
__device__ __forceinline__ float rcp(float x) { float y; asm("rcp.approx.ftz.f32 %0, %1;" : "=f"(y) : "f"(x)); return y; }
__device__ __forceinline__ void stmatrix_x4(uint32_t addr, uint32_t r0, uint32_t r1, uint32_t r2, uint32_t r3) {
  asm volatile("stmatrix.sync.aligned.m8n8.x4.shared.b16 [%0], {%1, %2, %3, %4};" ::"r"(addr), "r"(r0), "r"(r1), "r"(r2), "r"(r3) : "memory");
}
template <int N> __device__ __forceinline__ void fence_regs(float (&d)[N]) {
#pragma unroll
  for (int i = 0; i < N; i++) asm volatile("" : "+f"(d[i])::"memory");
}

template <int TA, int TB>
__device__ __forceinline__ void wgmma_m64n128k16_ss(float (&d)[64], uint64_t descA, uint64_t descB) {
  asm volatile("{\n.reg .pred p;\nsetp.ne.b32 p, 1, 0;\n"
    "wgmma.mma_async.sync.aligned.m64n128k16.f32.bf16.bf16 "
    "{%0, %1, %2, %3, %4, %5, %6, %7, %8, %9, %10, %11, %12, %13, %14, %15, %16, %17, %18, %19, %20, %21, %22, %23, %24, %25, %26, %27, %28, %29, %30, %31, %32, %33, %34, %35, %36, %37, %38, %39, %40, %41, %42, %43, %44, %45, %46, %47, %48, %49, %50, %51, %52, %53, %54, %55, %56, %57, %58, %59, %60, %61, %62, %63}, "
    "%64, %65, p, 1, 1, %66, %67;\n}\n"
    : "+f"(d[0]), "+f"(d[1]), "+f"(d[2]), "+f"(d[3]), "+f"(d[4]), "+f"(d[5]), "+f"(d[6]), "+f"(d[7]), "+f"(d[8]), "+f"(d[9]), "+f"(d[10]), "+f"(d[11]), "+f"(d[12]), "+f"(d[13]), "+f"(d[14]), "+f"(d[15]), "+f"(d[16]), "+f"(d[17]), "+f"(d[18]), "+f"(d[19]), "+f"(d[20]), "+f"(d[21]), "+f"(d[22]), "+f"(d[23]), "+f"(d[24]), "+f"(d[25]), "+f"(d[26]), "+f"(d[27]), "+f"(d[28]), "+f"(d[29]), "+f"(d[30]), "+f"(d[31]), "+f"(d[32]), "+f"(d[33]), "+f"(d[34]), "+f"(d[35]), "+f"(d[36]), "+f"(d[37]), "+f"(d[38]), "+f"(d[39]), "+f"(d[40]), "+f"(d[41]), "+f"(d[42]), "+f"(d[43]), "+f"(d[44]), "+f"(d[45]), "+f"(d[46]), "+f"(d[47]), "+f"(d[48]), "+f"(d[49]), "+f"(d[50]), "+f"(d[51]), "+f"(d[52]), "+f"(d[53]), "+f"(d[54]), "+f"(d[55]), "+f"(d[56]), "+f"(d[57]), "+f"(d[58]), "+f"(d[59]), "+f"(d[60]), "+f"(d[61]), "+f"(d[62]), "+f"(d[63])
    : "l"(descA), "l"(descB), "n"(TA), "n"(TB));
}

template <int TA, int TB>
__device__ __forceinline__ void wgmma_m64n32k16_ss(float (&d)[16], uint64_t descA, uint64_t descB) {
  asm volatile("{\n.reg .pred p;\nsetp.ne.b32 p, 1, 0;\n"
    "wgmma.mma_async.sync.aligned.m64n32k16.f32.bf16.bf16 "
    "{%0, %1, %2, %3, %4, %5, %6, %7, %8, %9, %10, %11, %12, %13, %14, %15}, "
    "%16, %17, p, 1, 1, %18, %19;\n}\n"
    : "+f"(d[0]), "+f"(d[1]), "+f"(d[2]), "+f"(d[3]), "+f"(d[4]), "+f"(d[5]), "+f"(d[6]), "+f"(d[7]), "+f"(d[8]), "+f"(d[9]), "+f"(d[10]), "+f"(d[11]), "+f"(d[12]), "+f"(d[13]), "+f"(d[14]), "+f"(d[15])
    : "l"(descA), "l"(descB), "n"(TA), "n"(TB));
}

template <int TA, int TB>
__device__ __forceinline__ void wgmma_m64n32k16_ss_init(float (&d)[16], uint64_t descA, uint64_t descB) {
  asm volatile("{\n.reg .pred p;\nsetp.ne.b32 p, 0, 0;\n"
    "wgmma.mma_async.sync.aligned.m64n32k16.f32.bf16.bf16 "
    "{%0, %1, %2, %3, %4, %5, %6, %7, %8, %9, %10, %11, %12, %13, %14, %15}, "
    "%16, %17, p, 1, 1, %18, %19;\n}\n"
    : "=f"(d[0]), "=f"(d[1]), "=f"(d[2]), "=f"(d[3]), "=f"(d[4]), "=f"(d[5]), "=f"(d[6]), "=f"(d[7]), "=f"(d[8]), "=f"(d[9]), "=f"(d[10]), "=f"(d[11]), "=f"(d[12]), "=f"(d[13]), "=f"(d[14]), "=f"(d[15])
    : "l"(descA), "l"(descB), "n"(TA), "n"(TB));
}

template <int TB>
__device__ __forceinline__ void wgmma_m64n32k16_rs(float (&d)[16], uint32_t a0, uint32_t a1, uint32_t a2, uint32_t a3, uint64_t descB) {
  asm volatile("{\n.reg .pred p;\nsetp.ne.b32 p, 1, 0;\n"
    "wgmma.mma_async.sync.aligned.m64n32k16.f32.bf16.bf16 "
    "{%0, %1, %2, %3, %4, %5, %6, %7, %8, %9, %10, %11, %12, %13, %14, %15}, "
    "{%16, %17, %18, %19}, %20, p, 1, 1, %21;\n}\n"
    : "+f"(d[0]), "+f"(d[1]), "+f"(d[2]), "+f"(d[3]), "+f"(d[4]), "+f"(d[5]), "+f"(d[6]), "+f"(d[7]), "+f"(d[8]), "+f"(d[9]), "+f"(d[10]), "+f"(d[11]), "+f"(d[12]), "+f"(d[13]), "+f"(d[14]), "+f"(d[15])
    : "r"(a0), "r"(a1), "r"(a2), "r"(a3), "l"(descB), "n"(TB));
}

template <int TB>
__device__ __forceinline__ void wgmma_m64n32k16_rs_init(float (&d)[16], uint32_t a0, uint32_t a1, uint32_t a2, uint32_t a3, uint64_t descB) {
  asm volatile("{\n.reg .pred p;\nsetp.ne.b32 p, 0, 0;\n"
    "wgmma.mma_async.sync.aligned.m64n32k16.f32.bf16.bf16 "
    "{%0, %1, %2, %3, %4, %5, %6, %7, %8, %9, %10, %11, %12, %13, %14, %15}, "
    "{%16, %17, %18, %19}, %20, p, 1, 1, %21;\n}\n"
    : "=f"(d[0]), "=f"(d[1]), "=f"(d[2]), "=f"(d[3]), "=f"(d[4]), "=f"(d[5]), "=f"(d[6]), "=f"(d[7]), "=f"(d[8]), "=f"(d[9]), "=f"(d[10]), "=f"(d[11]), "=f"(d[12]), "=f"(d[13]), "=f"(d[14]), "=f"(d[15])
    : "r"(a0), "r"(a1), "r"(a2), "r"(a3), "l"(descB), "n"(TB));
}

template <int TA, int TB>
__device__ __forceinline__ void wgmma_m64n40k16_ss(float (&d)[20], uint64_t descA, uint64_t descB) {
  asm volatile("{\n.reg .pred p;\nsetp.ne.b32 p, 1, 0;\n"
    "wgmma.mma_async.sync.aligned.m64n40k16.f32.bf16.bf16 "
    "{%0, %1, %2, %3, %4, %5, %6, %7, %8, %9, %10, %11, %12, %13, %14, %15, %16, %17, %18, %19}, "
    "%20, %21, p, 1, 1, %22, %23;\n}\n"
    : "+f"(d[0]), "+f"(d[1]), "+f"(d[2]), "+f"(d[3]), "+f"(d[4]), "+f"(d[5]), "+f"(d[6]), "+f"(d[7]), "+f"(d[8]), "+f"(d[9]), "+f"(d[10]), "+f"(d[11]), "+f"(d[12]), "+f"(d[13]), "+f"(d[14]), "+f"(d[15]), "+f"(d[16]), "+f"(d[17]), "+f"(d[18]), "+f"(d[19])
    : "l"(descA), "l"(descB), "n"(TA), "n"(TB));
}

template <int TA, int TB>
__device__ __forceinline__ void wgmma_m64n40k16_ss_init(float (&d)[20], uint64_t descA, uint64_t descB) {
  asm volatile("{\n.reg .pred p;\nsetp.ne.b32 p, 0, 0;\n"
    "wgmma.mma_async.sync.aligned.m64n40k16.f32.bf16.bf16 "
    "{%0, %1, %2, %3, %4, %5, %6, %7, %8, %9, %10, %11, %12, %13, %14, %15, %16, %17, %18, %19}, "
    "%20, %21, p, 1, 1, %22, %23;\n}\n"
    : "=f"(d[0]), "=f"(d[1]), "=f"(d[2]), "=f"(d[3]), "=f"(d[4]), "=f"(d[5]), "=f"(d[6]), "=f"(d[7]), "=f"(d[8]), "=f"(d[9]), "=f"(d[10]), "=f"(d[11]), "=f"(d[12]), "=f"(d[13]), "=f"(d[14]), "=f"(d[15]), "=f"(d[16]), "=f"(d[17]), "=f"(d[18]), "=f"(d[19])
    : "l"(descA), "l"(descB), "n"(TA), "n"(TB));
}

template <int TB>
__device__ __forceinline__ void wgmma_m64n40k16_rs(float (&d)[20], uint32_t a0, uint32_t a1, uint32_t a2, uint32_t a3, uint64_t descB) {
  asm volatile("{\n.reg .pred p;\nsetp.ne.b32 p, 1, 0;\n"
    "wgmma.mma_async.sync.aligned.m64n40k16.f32.bf16.bf16 "
    "{%0, %1, %2, %3, %4, %5, %6, %7, %8, %9, %10, %11, %12, %13, %14, %15, %16, %17, %18, %19}, "
    "{%20, %21, %22, %23}, %24, p, 1, 1, %25;\n}\n"
    : "+f"(d[0]), "+f"(d[1]), "+f"(d[2]), "+f"(d[3]), "+f"(d[4]), "+f"(d[5]), "+f"(d[6]), "+f"(d[7]), "+f"(d[8]), "+f"(d[9]), "+f"(d[10]), "+f"(d[11]), "+f"(d[12]), "+f"(d[13]), "+f"(d[14]), "+f"(d[15]), "+f"(d[16]), "+f"(d[17]), "+f"(d[18]), "+f"(d[19])
    : "r"(a0), "r"(a1), "r"(a2), "r"(a3), "l"(descB), "n"(TB));
}

template <int TB>
__device__ __forceinline__ void wgmma_m64n40k16_rs_init(float (&d)[20], uint32_t a0, uint32_t a1, uint32_t a2, uint32_t a3, uint64_t descB) {
  asm volatile("{\n.reg .pred p;\nsetp.ne.b32 p, 0, 0;\n"
    "wgmma.mma_async.sync.aligned.m64n40k16.f32.bf16.bf16 "
    "{%0, %1, %2, %3, %4, %5, %6, %7, %8, %9, %10, %11, %12, %13, %14, %15, %16, %17, %18, %19}, "
    "{%20, %21, %22, %23}, %24, p, 1, 1, %25;\n}\n"
    : "=f"(d[0]), "=f"(d[1]), "=f"(d[2]), "=f"(d[3]), "=f"(d[4]), "=f"(d[5]), "=f"(d[6]), "=f"(d[7]), "=f"(d[8]), "=f"(d[9]), "=f"(d[10]), "=f"(d[11]), "=f"(d[12]), "=f"(d[13]), "=f"(d[14]), "=f"(d[15]), "=f"(d[16]), "=f"(d[17]), "=f"(d[18]), "=f"(d[19])
    : "r"(a0), "r"(a1), "r"(a2), "r"(a3), "l"(descB), "n"(TB));
}


template <int MODE>
__device__ __forceinline__ void mainloop(float (&acc0)[64], float (&acc1)[64], int it0, int nkb, uint32_t sbase, int cw,
                                         uint32_t ord_parity) {
  const uint32_t bars = sbase + OFF_BAR;
  const int lane = threadIdx.x & 31;
  int stage = it0 % STAGES;
  uint32_t phase = (it0 / STAGES) & 1;
#pragma unroll
  for (int i = 0; i < 64; i++) { acc0[i] = 0.f; acc1[i] = 0.f; }
  mbar_wait(bars + B_ORD + 8 * cw, ord_parity);
  int prev = 0;
  for (int kb = 0; kb < nkb; kb++) {
    mbar_wait(bars + 8 * stage, phase);
    const uint32_t lo = ((sbase & 0x3FFFFu) + stage * STAGE_BYTES) >> 4;
    const uint32_t loK = lo | (1u << 16), loM = lo | (512u << 16);
    wgmma_fence();
#pragma unroll
    for (int k = 0; k < 4; k++) {
      if (MODE == 0) {
        const uint64_t dx = desc128(loK + 1024 + 2 * k);
        wgmma_m64n128k16_ss<0, 0>(acc0, desc128(loK + 2 * k), dx);
        wgmma_m64n128k16_ss<0, 0>(acc1, desc128(loK + 512 + 2 * k), dx);
      } else if (MODE == 1) {
        const uint64_t dw = desc128(loM + 128 * k);
        wgmma_m64n128k16_ss<0, 1>(acc0, desc128(loK + 1024 + 2 * k), dw);
        wgmma_m64n128k16_ss<0, 1>(acc1, desc128(loK + 1536 + 2 * k), dw);
      } else {
        const uint64_t dw = desc128(loK + 2 * k);
        wgmma_m64n128k16_ss<1, 0>(acc0, desc128(loM + 1024 + 128 * k), dw);
        wgmma_m64n128k16_ss<1, 0>(acc1, desc128(loM + 1536 + 128 * k), dw);
      }
      if (k == 1 && kb == nkb - 1 && (threadIdx.x & 127) == 0) mbar_arrive(bars + B_ORD + 8 * (cw ^ 1));
    }
    wgmma_commit();
    wgmma_wait<1>();
    if (kb > 0 && lane < 2) mbar_arrive_cluster(bars + B_EMPTY + 8 * prev, lane);
    prev = stage;
    if (++stage == STAGES) { stage = 0; phase ^= 1; }
  }
  wgmma_wait<0>();
  if (lane < 2) mbar_arrive_cluster(bars + B_EMPTY + 8 * prev, lane);
  fence_regs(acc0);
  fence_regs(acc1);
}

template <int N>
__device__ __forceinline__ void dual_softmax_n(const float (&p)[N][16], uint32_t (&pos)[N][8], uint32_t (&neg)[N][8]) {
  constexpr float L2E = 1.4426950408889634f;
  float ca[N][2], cb[N][2];
  {
    float mx[N][2], mn[N][2];
#pragma unroll
    for (int i = 0; i < N; i++)
#pragma unroll
      for (int r = 0; r < 2; r++) {
        const int o = 2 * r;
        mx[i][r] = fmaxf(fmaxf(fmaxf(p[i][o], p[i][o + 1]), fmaxf(p[i][4 + o], p[i][5 + o])),
                         fmaxf(fmaxf(p[i][8 + o], p[i][9 + o]), fmaxf(p[i][12 + o], p[i][13 + o])));
        mn[i][r] = fminf(fminf(fminf(p[i][o], p[i][o + 1]), fminf(p[i][4 + o], p[i][5 + o])),
                         fminf(fminf(p[i][8 + o], p[i][9 + o]), fminf(p[i][12 + o], p[i][13 + o])));
      }
#pragma unroll
    for (int o = 1; o <= 2; o <<= 1) {
      float tx[N][2], tn[N][2];
#pragma unroll
      for (int i = 0; i < N; i++)
#pragma unroll
        for (int r = 0; r < 2; r++) { tx[i][r] = __shfl_xor_sync(0xffffffffu, mx[i][r], o); tn[i][r] = __shfl_xor_sync(0xffffffffu, mn[i][r], o); }
#pragma unroll
      for (int i = 0; i < N; i++)
#pragma unroll
        for (int r = 0; r < 2; r++) { mx[i][r] = fmaxf(mx[i][r], tx[i][r]); mn[i][r] = fminf(mn[i][r], tn[i][r]); }
    }
#pragma unroll
    for (int i = 0; i < N; i++)
#pragma unroll
      for (int r = 0; r < 2; r++) { ca[i][r] = -mx[i][r] * L2E; cb[i][r] = mn[i][r] * L2E; }
  }
  float ep[2][16], en[2][16];
  float rp[2], rn[2];
#pragma unroll
  for (int i = 0; i <= N; i++) {
    const int cur = i & 1, prv = cur ^ 1;
    if (i > 0) {
      float sp[2], sn[2];
#pragma unroll
      for (int r = 0; r < 2; r++) {
        const int o = 2 * r;
        sp[r] = ((ep[prv][o] + ep[prv][o + 1]) + (ep[prv][4 + o] + ep[prv][5 + o])) + ((ep[prv][8 + o] + ep[prv][9 + o]) + (ep[prv][12 + o] + ep[prv][13 + o]));
        sn[r] = ((en[prv][o] + en[prv][o + 1]) + (en[prv][4 + o] + en[prv][5 + o])) + ((en[prv][8 + o] + en[prv][9 + o]) + (en[prv][12 + o] + en[prv][13 + o]));
      }
      float t0[2], t1[2];
#pragma unroll
      for (int r = 0; r < 2; r++) { t0[r] = __shfl_xor_sync(0xffffffffu, sp[r], 1); t1[r] = __shfl_xor_sync(0xffffffffu, sn[r], 1); }
      if (i < N) {
#pragma unroll
        for (int e = 0; e < 4; e++) {
          ep[cur][e] = ex2(fmaf(p[i][e], L2E, ca[i][e >> 1])); en[cur][e] = ex2(fmaf(p[i][e], -L2E, cb[i][e >> 1]));
        }
      }
#pragma unroll
      for (int r = 0; r < 2; r++) { sp[r] += t0[r]; sn[r] += t1[r]; }
#pragma unroll
      for (int r = 0; r < 2; r++) { t0[r] = __shfl_xor_sync(0xffffffffu, sp[r], 2); t1[r] = __shfl_xor_sync(0xffffffffu, sn[r], 2); }
      if (i < N) {
#pragma unroll
        for (int e = 4; e < 8; e++) {
          ep[cur][e] = ex2(fmaf(p[i][e], L2E, ca[i][(e >> 1) & 1])); en[cur][e] = ex2(fmaf(p[i][e], -L2E, cb[i][(e >> 1) & 1]));
        }
      }
#pragma unroll
      for (int r = 0; r < 2; r++) { rp[r] = rcp(sp[r] + t0[r]); rn[r] = rcp(sn[r] + t1[r]); }
    } else {
#pragma unroll
      for (int e = 0; e < 8; e++) {
        ep[cur][e] = ex2(fmaf(p[i][e], L2E, ca[i][(e >> 1) & 1])); en[cur][e] = ex2(fmaf(p[i][e], -L2E, cb[i][(e >> 1) & 1]));
      }
    }
#pragma unroll
    for (int j = 0; j < 4; j++) {
      if (i < N && j >= 2) {
#pragma unroll
        for (int e = 4 * j; e < 4 * j + 4; e++) {
          ep[cur][e] = ex2(fmaf(p[i][e], L2E, ca[i][(e >> 1) & 1])); en[cur][e] = ex2(fmaf(p[i][e], -L2E, cb[i][(e >> 1) & 1]));
        }
      }
      if (i > 0) {
#pragma unroll
        for (int r = 0; r < 2; r++) {
          pos[i - 1][2 * j + r] = pack_bf16(ep[prv][4 * j + 2 * r] * rp[r], ep[prv][4 * j + 2 * r + 1] * rp[r]);
          neg[i - 1][2 * j + r] = pack_bf16(en[prv][4 * j + 2 * r] * rn[r], en[prv][4 * j + 2 * r + 1] * rn[r]);
        }
      }
    }
  }
}

__device__ __forceinline__ float4 lds128(uint32_t addr) {
  float4 v;
  asm volatile("ld.shared.v4.f32 {%0, %1, %2, %3}, [%4];" : "=f"(v.x), "=f"(v.y), "=f"(v.z), "=f"(v.w) : "r"(addr) : "memory");
  return v;
}
__device__ __forceinline__ float2 lds64(uint32_t addr) {
  float2 v;
  asm volatile("ld.shared.v2.f32 {%0, %1}, [%2];" : "=f"(v.x), "=f"(v.y) : "r"(addr) : "memory");
  return v;
}
__device__ __forceinline__ void sts128(uint32_t addr, float a, float b, float c, float d) {
  asm volatile("st.shared.v4.f32 [%0], {%1, %2, %3, %4};" ::"r"(addr), "f"(a), "f"(b), "f"(c), "f"(d) : "memory");
}
struct cplx { float r, i; };
__device__ __forceinline__ cplx cmul(cplx a, cplx b) { return {a.r * b.r - a.i * b.i, a.r * b.i + a.i * b.r}; }
__device__ __forceinline__ cplx cfma(cplx a, cplx b, cplx c) {
  return {fmaf(a.r, b.r, fmaf(-a.i, b.i, c.r)), fmaf(a.r, b.i, fmaf(a.i, b.r, c.i))};
}
__device__ __forceinline__ cplx shfl_up_c(cplx v, int d) {
  return {__shfl_up_sync(0xffffffffu, v.r, d, 4), __shfl_up_sync(0xffffffffu, v.i, d, 4)};
}

struct ChanParams { cplx lam, c2, l32, l64, l128, g32, f512; };
constexpr int PSTRIDE = 80;

__device__ __forceinline__ void chan_params(float lr, float li, float log_dt, uint32_t dst) {
  const float dt = __bfloat162float(__float2bfloat16(expf(log_dt)));
  const float mag = expf(dt * lr);
  float sn, cs;
  sincosf(dt * li, &sn, &cs);
  const cplx lam = {mag * cs, mag * sn};
  const float nr = lam.r - 1.0f, ni = lam.i;
  const float den = lr * lr + li * li;
  const cplx c2 = {2.0f * (nr * lr + ni * li) / den, 2.0f * (ni * lr - nr * li) / den};
  cplx l = lam;
#pragma unroll 1
  for (int s = 0; s < 5; s++) l = cmul(l, l);
  const cplx l32 = l, l64 = cmul(l32, l32), l96 = cmul(l64, l32), l128 = cmul(l64, l64);
  const cplx l256 = cmul(l128, l128), l512 = cmul(l256, l256), l1024 = cmul(l512, l512), l1536 = cmul(l1024, l512);
  sts128(dst, lam.r, lam.i, c2.r, c2.i);
  sts128(dst + 16, l32.r, l32.i, l64.r, l64.i);
  sts128(dst + 32, l96.r, l96.i, l128.r, l128.i);
  sts128(dst + 48, l512.r, l512.i, l1024.r, l1024.i);
  sts128(dst + 64, l1536.r, l1536.i, 1.0f, 0.0f);
}
__device__ __forceinline__ ChanParams load_params(uint32_t src, int q) {
  ChanParams c;
  const float4 a = lds128(src), b = lds128(src + 16), d = lds128(src + 32);
  c.lam = {a.x, a.y}; c.c2 = {a.z, a.w}; c.l32 = {b.x, b.y}; c.l64 = {b.z, b.w}; c.l128 = {d.z, d.w};
  const float2 g = lds64(src + (q == 0 ? 72 : 8 + 8 * q)), f = lds64(src + (q == 0 ? 72 : 40 + 8 * q));
  c.g32 = {g.x, g.y}; c.f512 = {f.x, f.y};
  return c;
}

__device__ __forceinline__ void epi_bu(float (&are)[64], float (&aim)[64], const ChanParams (&cp)[2],
                                       uint32_t sbase, int G, int chunk, int cw, unsigned epoch) {
  const int lane = threadIdx.x & 31, w = (threadIdx.x & 127) >> 5, q = lane & 3, r8 = lane >> 2;
  cplx E[2] = {{0.f, 0.f}, {0.f, 0.f}};
#pragma unroll
  for (int k8 = 0; k8 < 16; k8++)
#pragma unroll
    for (int e = 0; e < 2; e++)
#pragma unroll
      for (int c = 0; c < 2; c++) E[c] = cfma(cp[c].lam, E[c], cplx{are[4 * k8 + 2 * c + e], aim[4 * k8 + 2 * c + e]});
  cplx prev[2];
#pragma unroll
  for (int c = 0; c < 2; c++) {
    cplx t = shfl_up_c(E[c], 1);
    if (q >= 1) E[c] = cfma(cp[c].l32, t, E[c]);
    t = shfl_up_c(E[c], 2);
    if (q >= 2) E[c] = cfma(cp[c].l64, t, E[c]);
    prev[c] = shfl_up_c(E[c], 1);
    if (q == 0) prev[c] = {0.f, 0.f};
  }
  uint4* gE = g_E + (size_t)G * 16 * 64 + 16 * w + r8;
  if (q == 3) {
    st_tagged(gE + chunk * 64, E[0].r, E[0].i, epoch);
    st_tagged(gE + chunk * 64 + 8, E[1].r, E[1].i, epoch);
  }
  cplx V[2][4];
  {
    unsigned long long w0[8], w1[8];
    unsigned pending = 0;
#pragma unroll
    for (int i = 0; i < 8; i++) {
      w0[i] = 0ull; w1[i] = 0ull;
      if (chunk - 1 - 4 * q - (i & 3) >= 0) pending |= 1u << i;
    }
    unsigned spins = 0;
    if (chunk > 0) __nanosleep(1000);
    while (true) {
#pragma unroll
      for (int i = 0; i < 8; i++)
        asm volatile("{\n.reg .pred p;\nsetp.ne.u32 p, %3, 0;\n@p ld.relaxed.gpu.global.v2.b64 {%0, %1}, [%2];\n}"
                     : "+l"(w0[i]), "+l"(w1[i]) : "l"(gE + (chunk - 1 - 4 * q - (i & 3)) * 64 + 8 * (i >> 2)), "r"(pending & (1u << i)) : "memory");
#pragma unroll
      for (int i = 0; i < 8; i++)
        if ((unsigned)(w0[i] >> 32) == epoch && (unsigned)(w1[i] >> 32) == epoch) pending &= ~(1u << i);
      if (__all_sync(0xffffffffu, pending == 0)) break;
      __nanosleep(500);
      if (give_up(sbase + OFF_BAR, ++spins)) break;
    }
#pragma unroll
    for (int i = 0; i < 8; i++) V[i >> 2][i & 3] = {__uint_as_float((unsigned)w0[i]), __uint_as_float((unsigned)w1[i])};
  }
  cplx s[2];
#pragma unroll
  for (int c = 0; c < 2; c++) {
    cplx Pq = V[c][3];
#pragma unroll
    for (int jj = 2; jj >= 0; jj--) Pq = cfma(cp[c].l128, Pq, V[c][jj]);
    Pq = cmul(Pq, cp[c].f512);
#pragma unroll
    for (int o = 1; o <= 2; o <<= 1) {
      Pq.r += __shfl_xor_sync(0xffffffffu, Pq.r, o);
      Pq.i += __shfl_xor_sync(0xffffffffu, Pq.i, o);
    }
    s[c] = cfma(cp[c].g32, Pq, prev[c]);
  }
  if (cw == 1) mbar_wait(sbase + OFF_BAR + B_EBF, 0);
#pragma unroll
  for (int qq = 0; qq < 4; qq++) {
    uint32_t ore[2][4], oim[2][4];
#pragma unroll
    for (int kk = 0; kk < 4; kk++) {
      const int k8 = 4 * qq + kk;
      float hr[2][2], hi[2][2];
#pragma unroll
      for (int e = 0; e < 2; e++)
#pragma unroll
        for (int c = 0; c < 2; c++) {
          s[c] = cfma(cp[c].lam, s[c], cplx{are[4 * k8 + 2 * c + e], aim[4 * k8 + 2 * c + e]});
          hr[c][e] = fmaf(cp[c].c2.r, s[c].r, -cp[c].c2.i * s[c].i);
          hi[c][e] = -fmaf(cp[c].c2.r, s[c].i, cp[c].c2.i * s[c].r);
        }
#pragma unroll
      for (int c = 0; c < 2; c++) {
        ore[c][kk] = pack_bf16(hr[c][0], hr[c][1]);
        oim[c][kk] = pack_bf16(hi[c][0], hi[c][1]);
      }
    }
#pragma unroll
    for (int c = 0; c < 2; c++) {
      const int row = 16 * w + r8 + 8 * c;
      const uint32_t addr = sbase + OFF_PHI + (qq >> 1) * 8192 + row * 128 + ((((qq & 1) * 4 + q) ^ (row & 7)) << 4);
      asm volatile("st.shared.v4.b32 [%0], {%1, %2, %3, %4};" ::"r"(addr), "r"(ore[c][0]), "r"(ore[c][1]), "r"(ore[c][2]), "r"(ore[c][3]) : "memory");
      asm volatile("st.shared.v4.b32 [%0], {%1, %2, %3, %4};" ::"r"(addr + 32768), "r"(oim[c][0]), "r"(oim[c][1]), "r"(oim[c][2]), "r"(oim[c][3]) : "memory");
    }
  }
  fence_async_smem();
  wg_bar(1 + cw);
  if ((threadIdx.x & 127) == 0) mbar_arrive(sbase + OFF_BAR + B_JOB + 8 * cw);
}

__device__ __forceinline__ void q_issue_num(float (&num)[20], const uint32_t (&pos)[8], const uint32_t (&neg)[8], uint32_t b) {
  wgmma_fence();
  wgmma_m64n40k16_rs_init<1>(num, pos[0], pos[1], pos[2], pos[3], make_desc(b, 640, 128, 0));
  wgmma_m64n40k16_rs<1>(num, pos[4], pos[5], pos[6], pos[7], make_desc(b + 1280, 640, 128, 0));
  wgmma_m64n40k16_rs<1>(num, neg[0], neg[1], neg[2], neg[3], make_desc(b + 2560, 640, 128, 0));
  wgmma_m64n40k16_rs<1>(num, neg[4], neg[5], neg[6], neg[7], make_desc(b + 3840, 640, 128, 0));
  wgmma_commit();
}
__device__ __forceinline__ void q_store_o(const float (&num)[20], uint32_t rowaddr, int chunk0) {
  const int lane = threadIdx.x & 31, mi = lane >> 3, rin = lane & 7;
  const float d0 = __shfl_sync(0xffffffffu, num[16], lane & ~3), d1 = __shfl_sync(0xffffffffu, num[18], lane & ~3);
  const float i0 = __fdividef(1.0f, d0 + 1e-6f), i1 = __fdividef(1.0f, d1 + 1e-6f);
#pragma unroll
  for (int jp = 0; jp < 2; jp++) {
    const int c0 = chunk0 + jp * 2 + (mi >> 1);
    stmatrix_x4(rowaddr + ((c0 ^ rin) << 4), pack_bf16(num[8 * jp] * i0, num[8 * jp + 1] * i0),
                pack_bf16(num[8 * jp + 2] * i1, num[8 * jp + 3] * i1), pack_bf16(num[8 * jp + 4] * i0, num[8 * jp + 5] * i0),
                pack_bf16(num[8 * jp + 6] * i1, num[8 * jp + 7] * i1));
  }
}
__device__ __forceinline__ void epi_attn(float (&acc0)[64], float (&acc1)[64], uint32_t sbase, int cw, bool isq) {
  const int t = threadIdx.x & 127, lane = t & 31, w = t >> 5, q = lane & 3, r8 = lane >> 2;
  const int mi = lane >> 3, rin = lane & 7;
  const int row0 = w * 16 + (mi & 1) * 8 + rin;
  uint32_t kf[2][16];
  if (isq) {
#pragma unroll
    for (int j = 0; j < 16; j += 2) {
      const uint32_t addr = sbase + OFF_PHI + (j >> 3) * 16384 + row0 * 128 + ((((j & 7) + (mi >> 1)) ^ rin) << 4);
      stmatrix_x4(addr, pack_bf16(acc0[4 * j], acc0[4 * j + 1]), pack_bf16(acc0[4 * j + 2], acc0[4 * j + 3]),
                  pack_bf16(acc0[4 * j + 4], acc0[4 * j + 5]), pack_bf16(acc0[4 * j + 6], acc0[4 * j + 7]));
      stmatrix_x4(addr + 8192, pack_bf16(acc1[4 * j], acc1[4 * j + 1]), pack_bf16(acc1[4 * j + 2], acc1[4 * j + 3]),
                  pack_bf16(acc1[4 * j + 4], acc1[4 * j + 5]), pack_bf16(acc1[4 * j + 6], acc1[4 * j + 7]));
    }
#pragma unroll
    for (int i = 0; i < 16; i++) { kf[0][i] = 0; kf[1][i] = 0; }
  } else {
#pragma unroll
    for (int j = 8; j < 16; j += 2) {
      const uint32_t addr = sbase + OFF_PHI + 16384 + ((j - 8) >> 2) * 8192 + row0 * 64 + ((((j & 3) + (mi >> 1)) ^ ((row0 >> 1) & 3)) << 4);
      stmatrix_x4(addr, pack_bf16(acc0[4 * j], acc0[4 * j + 1]), pack_bf16(acc0[4 * j + 2], acc0[4 * j + 3]),
                  pack_bf16(acc0[4 * j + 4], acc0[4 * j + 5]), pack_bf16(acc0[4 * j + 6], acc0[4 * j + 7]));
      stmatrix_x4(addr + 4096, pack_bf16(acc1[4 * j], acc1[4 * j + 1]), pack_bf16(acc1[4 * j + 2], acc1[4 * j + 3]),
                  pack_bf16(acc1[4 * j + 4], acc1[4 * j + 5]), pack_bf16(acc1[4 * j + 6], acc1[4 * j + 7]));
    }
#pragma unroll
    for (int i = 0; i < 16; i++) {
      kf[0][i] = pack_bf16(acc0[2 * i], acc0[2 * i + 1]);
      kf[1][i] = pack_bf16(acc1[2 * i], acc1[2 * i + 1]);
    }
  }
  fence_async_smem();
  wg_bar(1 + cw);
  const int nsub = isq ? 2 : 1;
#pragma unroll 1
  for (int sub = 0; sub < nsub; sub++) {
    const uint32_t tile = sbase + OFF_PHI + sub * 16384;
    const uint32_t wp = sbase + OFF_WPHI + (isq ? 2 * sub : 2 * cw) * 2048;
    float pq[4][16];
    uint32_t pos[4][8], neg[4][8];
    if (isq) {
      wgmma_fence();
#pragma unroll
      for (int i = 0; i < 4; i++) {
        const uint32_t a = tile + (i & 1) * 8192 + (i >> 1) * 64, b = wp + (i >> 1) * 2048;
        wgmma_m64n32k16_ss_init<0, 1>(pq[i], make_desc(a, 16, 1024, 1), make_desc(b, 512, 512, 2));
        wgmma_m64n32k16_ss<0, 1>(pq[i], make_desc(a + 32, 16, 1024, 1), make_desc(b + 1024, 512, 512, 2));
      }
    } else {
      wgmma_fence();
#pragma unroll
      for (int i = 0; i < 4; i++) {
        const uint32_t b = wp + (i >> 1) * 2048;
        const uint32_t* f = &kf[i & 1][8 * (i >> 1)];
        wgmma_m64n32k16_rs_init<1>(pq[i], f[0], f[1], f[2], f[3], make_desc(b, 512, 512, 2));
        wgmma_m64n32k16_rs<1>(pq[i], f[4], f[5], f[6], f[7], make_desc(b + 1024, 512, 512, 2));
      }
    }
    wgmma_commit();
    wgmma_wait<0>();
#pragma unroll
    for (int i = 0; i < 4; i++) fence_regs(pq[i]);
    dual_softmax_n<4>(pq, pos, neg);
    if (!isq) {
      float kvacc[2][20];
      mbar_wait(sbase + OFF_BAR + B_EBF + 8 + 8 * cw, 0);
#pragma unroll
      for (int hh = 0; hh < 2; hh++) {
#pragma unroll
        for (int half = 0; half < 2; half++) {
          const uint32_t rb = sbase + OFF_PHI + hh * 32768 + (half * 64 + row0) * 128;
#pragma unroll
          for (int jp = 0; jp < 2; jp++) {
            const int c0 = jp * 2 + (mi >> 1), i = 2 * hh + half;
            stmatrix_x4(rb + ((c0 ^ rin) << 4), pos[i][4 * jp], pos[i][4 * jp + 1], pos[i][4 * jp + 2], pos[i][4 * jp + 3]);
            stmatrix_x4(rb + (((c0 + 4) ^ rin) << 4), neg[i][4 * jp], neg[i][4 * jp + 1], neg[i][4 * jp + 2], neg[i][4 * jp + 3]);
          }
        }
      }
      fence_async_smem();
      wg_bar(1 + cw);
      wgmma_fence();
#pragma unroll
      for (int hh = 0; hh < 2; hh++)
#pragma unroll
        for (int ks = 0; ks < 8; ks++) {
          const uint32_t vb = sbase + OFF_PHI + 16384 + hh * 8192 + ks * 1024;
          const uint64_t da = make_desc(sbase + OFF_PHI + hh * 32768 + ks * 2048, 1024, 1024, 1);
          const uint64_t db = make_desc(vb, sbase + OFF_ONES - vb, 512, 2);
          if (ks == 0) wgmma_m64n40k16_ss_init<1, 1>(kvacc[hh], da, db);
          else wgmma_m64n40k16_ss<1, 1>(kvacc[hh], da, db);
        }
      wgmma_commit();
      wgmma_wait<0>();
      fence_regs(kvacc[0]);
      fence_regs(kvacc[1]);
      wg_bar(1 + cw);
      if (t == 0) mbar_arrive(sbase + OFF_BAR + B_EBA + 8 * cw);
#pragma unroll
      for (int hh = 0; hh < 2; hh++) {
        const uint32_t dst = sbase + OFF_V + hh * 10240 + ((16 * w + r8) * KVW + 2 * q) * 4;
#pragma unroll
        for (int j = 0; j < 5; j++) {
          asm volatile("st.shared.v2.f32 [%0], {%1, %2};" ::"r"(dst + 32 * j), "f"(kvacc[hh][4 * j]), "f"(kvacc[hh][4 * j + 1]) : "memory");
          asm volatile("st.shared.v2.f32 [%0], {%1, %2};" ::"r"(dst + 8 * KVW * 4 + 32 * j), "f"(kvacc[hh][4 * j + 2]), "f"(kvacc[hh][4 * j + 3]) : "memory");
        }
      }
      fence_async_smem();
      wg_bar(1 + cw);
      if (t == 0) mbar_arrive(sbase + OFF_BAR + B_JOB + 16 + 8 * cw);
    } else {
      float num[4][20];
      mbar_wait(sbase + OFF_BAR + B_KVX + 8 * sub, 0);
#pragma unroll
      for (int i = 0; i < 4; i++) q_issue_num(num[i], pos[i], neg[i], sbase + OFF_V + (2 * sub + (i >> 1)) * 5120);
      wgmma_wait<2>();
      fence_regs(num[0]); fence_regs(num[1]);
      q_store_o(num[0], tile + row0 * 128, 0);
      q_store_o(num[1], tile + 8192 + row0 * 128, 0);
      wgmma_wait<0>();
      fence_regs(num[2]); fence_regs(num[3]);
      q_store_o(num[2], tile + row0 * 128, 4);
      q_store_o(num[3], tile + 8192 + row0 * 128, 4);
      fence_async_smem();
      wg_bar(1);
      if (t == 0) mbar_arrive(sbase + OFF_BAR + B_JOB + 32 + 8 * sub);
    }
  }
}

__device__ __forceinline__ void helper_kv(uint32_t sbase, int g, unsigned epoch) {
  const int h = threadIdx.x - 64;
  mbar_wait_long(sbase + OFF_BAR + B_EBF + 24, 0);
#pragma unroll 1
  for (int pr = 0; pr < 2; pr++) {
    if ((h & 31) == 0) {
      wait_ge(sbase + OFF_BAR, &g_flags.kvcnt[(g + 8 * pr) * 8], 16u * epoch);
    }
    __syncwarp();
    const float4* src = reinterpret_cast<const float4*>(g_kv + (size_t)(2 * g + 16 * pr) * 64 * KVW);
#pragma unroll 1
    for (int ib = 0; ib < 3; ib++) {
      float4 u[7];
#pragma unroll
      for (int i = 0; i < 7; i++) u[i] = __ldcg(src + min((ib * 7 + i) * 64 + h, 1279));
#pragma unroll
      for (int i = 0; i < 7; i++) {
        const int idx = min((ib * 7 + i) * 64 + h, 1279);
        const int f2 = idx / 10, j = idx - f2 * 10;
        const uint32_t dst = sbase + OFF_V + pr * 10240 + (f2 >> 3) * 640 + (j >> 1) * 128 + (f2 & 7) * 16 + (j & 1) * 8;
        asm volatile("st.shared.v2.b32 [%0], {%1, %2};" ::"r"(dst), "r"(pack_bf16(u[i].x, u[i].y)), "r"(pack_bf16(u[i].z, u[i].w)) : "memory");
      }
    }
    fence_async_smem();
    __syncwarp();
    if ((h & 31) == 0) mbar_arrive(sbase + OFF_BAR + B_KVX + 8 * pr);
  }
}

__device__ __forceinline__ void store_agent(const Params& prm, uint32_t sbase, int g, int rb, unsigned epoch) {
  const uint32_t bars = sbase + OFF_BAR;
  wait_ge(bars, &g_flags.zero_cnt, 128u * epoch);
  fence_async_global();
#pragma unroll 1
  for (int j = 0; j < 6; j++) {
    mbar_wait_long(bars + B_JOB + 8 * j, 0);
    unsigned* flag;
    if (j < 2) {
      const int G = g + 8 * j;
#pragma unroll 1
      for (int u = 0; u < 16; u++) {
        tma_store_3d(&prm.tmHTs, sbase + OFF_PHI + (u & 7) * 2048 + (u >> 3) * 32768, 0, (u >> 3) * 1024 + 64 * G + (u & 3) * 16, 2 * rb + ((u >> 2) & 1));
        __nanosleep(50);
      }
      flag = &g_flags.hcnt[rb * 8];
    } else if (j < 4) {
      const int hp = g + 8 * (j - 2);
#pragma unroll 1
      for (int u = 0; u < 10; u++) {
        const uint32_t o = u * 2048;
        const uint32_t src = sbase + OFF_V + o;
        bulk_reduce_f32(g_kv + (size_t)(2 * hp) * 64 * KVW + o / 4, src, 2048);
        if (j == 2) __nanosleep(50);
      }
      flag = &g_flags.kvcnt[hp * 8];
    } else {
      tma_store_2d(&prm.tmO, sbase + OFF_PHI + (j - 4) * 16384, 64 * (g + 8 * (j - 4)), 128 * rb);
      flag = &g_flags.ocnt[(2 * rb + (j - 4)) * 8];
    }
    bulk_commit();
    if (j != 4) {
      bulk_wait_read();
      mbar_arrive(bars + B_EBF + 8 * (j < 4 ? j : 4));
    }
    bulk_wait_all();
    red_relaxed_add(flag, 1);
  }
}

constexpr int OST = 544;
__device__ __forceinline__ void stage_half(const float (&a)[64], uint32_t wbuf) {
  const int lane = threadIdx.x & 31, q = lane & 3, r8 = lane >> 2;
#pragma unroll
  for (int j = 0; j < 16; j++) {
    asm volatile("st.shared.v2.f32 [%0], {%1, %2};" ::"r"(wbuf + r8 * OST + j * 32 + q * 8), "f"(a[4 * j]), "f"(a[4 * j + 1]) : "memory");
    asm volatile("st.shared.v2.f32 [%0], {%1, %2};" ::"r"(wbuf + (r8 + 8) * OST + j * 32 + q * 8), "f"(a[4 * j + 2]), "f"(a[4 * j + 3]) : "memory");
  }
  __syncwarp();
}
__device__ __forceinline__ void store_y(float (&acc0)[64], const float (&acc1)[64], uint32_t wbuf, const Params& prm, int rb, int g) {
  const int lane = threadIdx.x & 31, w = (threadIdx.x & 127) >> 5;
  const uint2 dk = __ldg(reinterpret_cast<const uint2*>(prm.dskip + 128 * g) + lane);
#pragma unroll 1
  for (int half = 0; half < 2; half++) {
    const int m0 = 64 * half + 16 * w;
    const int t0 = rb * 128 + 32 * ((m0 >> 3) & 3) + 8 * (m0 >> 5);
    uint2 xs[16];
#pragma unroll
    for (int r = 0; r < 16; r++)
      xs[r] = __ldg(reinterpret_cast<const uint2*>(prm.xB + (size_t)(t0 + (r & 7) + (r >> 3) * 32) * DM + 128 * g) + lane);
    stage_half(acc0, wbuf);
    float* dst = prm.out + (size_t)t0 * 2048 + 1024 + 128 * g + 4 * lane;
#pragma unroll
    for (int r = 0; r < 16; r++) {
      float4 v = lds128(wbuf + r * OST + lane * 16);
      const float2 s0 = __bfloat1622float2(__hmul2(*reinterpret_cast<const __nv_bfloat162*>(&xs[r].x), *reinterpret_cast<const __nv_bfloat162*>(&dk.x)));
      const float2 s1 = __bfloat1622float2(__hmul2(*reinterpret_cast<const __nv_bfloat162*>(&xs[r].y), *reinterpret_cast<const __nv_bfloat162*>(&dk.y)));
      v.x += s0.x; v.y += s0.y; v.z += s1.x; v.w += s1.y;
      __stcs(reinterpret_cast<float4*>(dst + (size_t)((r & 7) + (r >> 3) * 32) * 2048), v);
    }
    __syncwarp();
#pragma unroll
    for (int i = 0; i < 64; i++) acc0[i] = acc1[i];
  }
}
__device__ __forceinline__ void drain_out(uint32_t wbuf, float* dst  ) {
  const int lane = threadIdx.x & 31;
#pragma unroll
  for (int r = 0; r < 16; r++) {
    const float4 v = lds128(wbuf + r * OST + lane * 16);
    const uint32_t p0 = pack_bf16(v.x, v.y), p1 = pack_bf16(v.z, v.w);
    __stcs(reinterpret_cast<float4*>(dst + (size_t)r * 2048) + lane,
           make_float4(__uint_as_float(p0 << 16), __uint_as_float(p0 & 0xffff0000u), __uint_as_float(p1 << 16), __uint_as_float(p1 & 0xffff0000u)));
  }
}

__global__ void __launch_bounds__(384, 1) fused_kernel(const __grid_constant__ Params prm) {
  extern __shared__ uint8_t smem_raw[];
  const uint32_t sbase = (smem_u32(smem_raw) + 1023) & ~1023u;
  const uint32_t bars = sbase + OFF_BAR;
  const int tid = threadIdx.x, wg = __shfl_sync(0xffffffffu, tid >> 7, 0);
  const int cl = blockIdx.x >> 1, rank = blockIdx.x & 1;
  const int g = cl >> 3, rb = 2 * (cl & 7) + rank;

  if (tid == 0) {
    for (int s = 0; s < STAGES; s++) { mbar_init(bars + 8 * s, 1);
      mbar_init(bars + B_EMPTY + 8 * s, 8);
    }
    mbar_init(bars + B_ORD, 1); mbar_init(bars + B_ORD + 8, 1); mbar_init(bars + B_WPHI, 1); mbar_init(bars + B_EPOCH, 1); mbar_init(bars + B_KVX, 2); mbar_init(bars + B_KVX + 8, 2);
    for (int j = 0; j < 6; j++) mbar_init(bars + B_JOB + 8 * j, 1);
    mbar_init(bars + B_PARAM, 2); mbar_init(bars + B_EBA, 1); mbar_init(bars + B_EBA + 8, 1);
    for (int j = 0; j < 5; j++) mbar_init(bars + B_EBF + 8 * j, 1);
    asm volatile("st.shared.u32 [%0], %1;" ::"r"(bars + B_DEAD), "r"(0u) : "memory");
    asm volatile("fence.mbarrier_init.release.cluster;" ::: "memory");
    asm volatile("fence.proxy.async.shared::cta;" ::: "memory");
#pragma unroll 1
    for (int kb = 0; kb < STAGES; kb++) {
      const uint32_t full = bars + 8 * kb, sw = sbase + kb * STAGE_BYTES;
      mbar_expect_tx(full, STAGE_BYTES);
      tma_5d(sw + 16384, &prm.tmXB, kb * 64, 0, 0, 0, rb, full);
      tma_2d(sw, &prm.tmBre, kb * 64, 64 * g, full);
      tma_2d(sw + 8192, &prm.tmBim, kb * 64, 64 * g, full);
    }
  } else if (tid == 32) {
    prefetch_tm(&prm.tmXB); prefetch_tm(rank ? &prm.tmBim : &prm.tmBre); prefetch_tm(&prm.tmWphi);
    prefetch_tm(&prm.tmXA); prefetch_tm(&prm.tmWqkv); prefetch_tm(&prm.tmHT);
    prefetch_tm(&prm.tmCre); prefetch_tm(&prm.tmCim); prefetch_tm(&prm.tmO); prefetch_tm(&prm.tmWo);
  } else if (tid >= 64 && tid < 128) {
    asm volatile("st.shared.v4.b32 [%0], {%1, %2, %2, %2};" ::"r"(sbase + OFF_ONES + (tid - 64) * 16), "r"(0x00003F80u), "r"(0u) : "memory");
    fence_async_smem();
  }
  __syncthreads();
  asm volatile("barrier.cluster.arrive.relaxed.aligned;\nbarrier.cluster.wait.acquire.aligned;" ::: "memory");

  if (wg == 0) {
    reg_dealloc<56>();
    const int warp = __shfl_sync(0xffffffffu, tid >> 5, 0), lane = tid & 31;
    if (warp == 0) {
      const bool leader = elect_one();
      if (leader) {
        mbar_expect_tx(bars + B_WPHI, 8192);
        tma_2d(sbase + OFF_WPHI, &prm.tmWphi, 0, 64 * g, bars + B_WPHI);
        tma_2d(sbase + OFF_WPHI + 4096, &prm.tmWphi, 0, 64 * g + 512, bars + B_WPHI);
      }
      int stage = 0;
      uint32_t phase = 0;
      unsigned epoch = 0;
      auto run = [&](auto kind, const CUtensorMap* tw, int w0, const CUtensorMap* tx, int kb0, int kb1) {
        constexpr int KIND = decltype(kind)::value;
#pragma unroll 1
        for (int kb = kb0; kb < kb1; kb++) {
          mbar_wait(bars + B_EMPTY + 8 * stage, phase);

          if (leader) {
            const uint32_t full = bars + 8 * stage;
            const uint32_t sw = sbase + stage * STAGE_BYTES;
            mbar_expect_tx(full, STAGE_BYTES);
            if (KIND == 0) {
              tma_2d_mc(sw + rank * 8192, tw, kb * 64, w0, full);
              tma_5d(sw + 16384, tx, kb * 64, 0, 0, 0, rb, full);
            } else if (KIND == 1) {
              tma_2d_mc(sw + rank * 8192, tw, w0, kb * 64, full);
              tma_2d(sw + 16384, tx, kb * 64, rb * 128, full);
            } else {
              tma_2d_mc(sw + rank * 8192, tw, (kb & 15) * 64, w0, full);
              tma_3d(sw + 16384, tx, 0, kb * 64, 2 * rb, full);
            }
          }
          if (++stage == STAGES) { stage = 0; phase ^= 1; }
        }
      };
      using K0 = std::integral_constant<int, 0>;
      using K1 = std::integral_constant<int, 1>;
      using K2 = std::integral_constant<int, 2>;
#pragma unroll 1
      for (int i = 0; i < 2; i++) run(K0{}, rank ? &prm.tmBim : &prm.tmBre, 64 * (g + 8 * i), &prm.tmXB, i == 0 ? STAGES : 0, 16);
#pragma unroll 1
      for (int i = 0; i < 3; i++)
        run(K1{}, &prm.tmWqkv, i < 2 ? 1024 + rank * 1024 + 64 * (g + 8 * i) : 64 * (g + 8 * rank), &prm.tmXA, 0, 16);
      mbar_wait(bars + B_EPOCH, 0);
      asm volatile("ld.shared.u32 %0, [%1];" : "=r"(epoch) : "r"(bars + B_EPOCHV) : "memory");
      wait_ge(bars, &g_flags.hcnt[rb * 8], 16u * epoch);
      fence_async_global();
#pragma unroll 1
      for (int i = 0; i < 2; i++) run(K2{}, i ? &prm.tmCim : &prm.tmCre, 128 * g + 64 * rank, &prm.tmHT, 16 * i, 16 * i + 16);
#pragma unroll 1
      for (int i = 0; i < 2; i++) {
        wait_ge(bars, &g_flags.ocnt[(2 * rb + i) * 8], 8u * epoch);
        fence_async_global();
        run(K1{}, &prm.tmWo, 128 * g + 64 * rank, &prm.tmO, 8 * i, 8 * i + 8);
      }
    } else if (warp == 1) {
      unsigned epoch = 0;
      if (lane == 0) {
        epoch = (atomicAdd(&g_flags.ticket, 1u) >> 7) + 1u;
        asm volatile("st.shared.u32 [%0], %1;" ::"r"(bars + B_EPOCHV), "r"(epoch) : "memory");
        mbar_arrive(bars + B_EPOCH);
      }
      uint4* z = reinterpret_cast<uint4*>(g_kv) + blockIdx.x * 160;
#pragma unroll
      for (int i = 0; i < 5; i++) __stcg(z + i * 32 + lane, make_uint4(0, 0, 0, 0));
      __syncwarp();
      if (lane == 0) {
        red_release_add(&g_flags.zero_cnt, 1);
        store_agent(prm, sbase, g, rb, epoch);
      }
    } else {
#pragma unroll 1
      for (int c = 0; c < 2; c++) {
        const int ch = tid - 64, p = 64 * (g + 8 * c) + ch;
        chan_params(__bfloat162float(prm.lam_re[p]), __bfloat162float(prm.lam_im[p]), __bfloat162float(prm.log_dt[p]),
                    sbase + OFF_PHI + 16384 + (c * 64 + ch) * PSTRIDE);
      }
      __syncwarp();
      if (lane == 0) mbar_arrive(bars + B_PARAM);
      unsigned epoch;
      mbar_wait(bars + B_EPOCH, 0);
      asm volatile("ld.shared.u32 %0, [%1];" : "=r"(epoch) : "r"(bars + B_EPOCHV) : "memory");
      helper_kv(sbase, g, epoch);
    }
    __syncwarp();
    asm volatile("barrier.cluster.arrive.relaxed.aligned;\nbarrier.cluster.wait.aligned;" ::: "memory");
  } else {
    reg_alloc<224>();
    const int cw = wg - 1;
    const int t = tid & 127, lane = t & 31, w = t >> 5, r8 = lane >> 2;
    float acc0[64], acc1[64];
    unsigned epoch;
    {
      const int G = g + 8 * cw;
      ChanParams cp[2];
      const uint32_t ptab = sbase + OFF_PHI + 16384 + (cw * 64 + 16 * w + r8) * PSTRIDE;
      if (cw == 1) {
        mbar_wait(bars + B_PARAM, 0);
#pragma unroll
        for (int c = 0; c < 2; c++) cp[c] = load_params(ptab + 8 * c * PSTRIDE, lane & 3);
      }
      mainloop<0>(acc0, acc1, 16 * cw, 16, sbase, cw, cw ^ 1);
      if (cw == 0) {
        mbar_wait(bars + B_PARAM, 0);
#pragma unroll
        for (int c = 0; c < 2; c++) cp[c] = load_params(ptab + 8 * c * PSTRIDE, lane & 3);
      }
      mbar_wait(bars + B_EPOCH, 0);
      asm volatile("ld.shared.u32 %0, [%1];" : "=r"(epoch) : "r"(bars + B_EPOCHV) : "memory");
      epi_bu(acc0, acc1, cp, sbase, G, rb, cw, epoch);
    }
#pragma unroll 1
    for (int step = 0; step < 3; step++) {
      const int it0 = cw ? 48 : (step == 0 ? 32 : (step == 1 ? 64 : 112));
      mainloop<1>(acc0, acc1, it0, 16, sbase, cw, cw ? 1 : (step & 1));
      if (step == 2) {
        stage_half(acc1, sbase + (4 + w) * 16 * OST);
        asm volatile("bar.arrive 3, 256;" ::: "memory");
        stage_half(acc0, sbase + w * 16 * OST);
        drain_out(sbase + w * 16 * OST, prm.out + (size_t)(rb * 128 + 16 * w) * 2048 + 128 * g);
        break;
      }
      mbar_wait(bars + B_WPHI, 0);
      if (cw == 1) {
        mbar_wait(bars + B_EBA, 0);
      } else if (step == 1) {
        mbar_wait(bars + B_EBA + 8, 0);
      }
      epi_attn(acc0, acc1, sbase, cw, step == 1);
      if (cw == 1) break;
    }
    if (cw == 1) {
      mainloop<2>(acc0, acc1, 80, 32, sbase, 1, 0);
      mbar_wait(bars + B_EBF + 32, 0);
      store_y(acc0, acc1, sbase + OFF_EB + w * 16 * OST, prm, rb, g);
      asm volatile("bar.sync 3, 256;" ::: "memory");
      drain_out(sbase + (4 + w) * 16 * OST, prm.out + (size_t)(rb * 128 + 64 + 16 * w) * 2048 + 128 * g);
    }
    asm volatile("barrier.cluster.arrive.relaxed.aligned;\nbarrier.cluster.wait.aligned;" ::: "memory");
  }
}

typedef CUresult (*PFN_encodeTiled)(CUtensorMap*, CUtensorMapDataType, cuuint32_t, void*, const cuuint64_t*, const cuuint64_t*,
                                    const cuuint32_t*, const cuuint32_t*, CUtensorMapInterleave, CUtensorMapSwizzle,
                                    CUtensorMapL2promotion, CUtensorMapFloatOOBfill);

bool make_tm(PFN_encodeTiled enc, CUtensorMap* tm, const void* base, int rank, const uint64_t* dims, const uint64_t* strides,
             const uint32_t* box, CUtensorMapSwizzle sw) {
  cuuint64_t gd[5], gs[5];
  cuuint32_t bx[5], es[5];
  for (int i = 0; i < rank; i++) { gd[i] = dims[i]; bx[i] = box[i]; es[i] = 1; }
  for (int i = 0; i + 1 < rank; i++) gs[i] = strides[i];
  return enc(tm, CU_TENSOR_MAP_DATA_TYPE_BFLOAT16, rank, const_cast<void*>(base), gd, gs, bx, es, CU_TENSOR_MAP_INTERLEAVE_NONE, sw,
             CU_TENSOR_MAP_L2_PROMOTION_L2_256B, CU_TENSOR_MAP_FLOAT_OOB_FILL_NONE) == CUDA_SUCCESS;
}
bool make_tm2(PFN_encodeTiled enc, CUtensorMap* tm, const void* base, uint64_t inner, uint64_t outer, uint32_t b0, uint32_t b1,
              CUtensorMapSwizzle sw = CU_TENSOR_MAP_SWIZZLE_128B) {
  const uint64_t dims[2] = {inner, outer}, str[1] = {inner * 2};
  const uint32_t box[2] = {b0, b1};
  return make_tm(enc, tm, base, 2, dims, str, box, sw);
}

}

extern "C" void kernel_launch(void* const* d_in, const int* in_sizes, int n_in, void* d_out, int out_size) {
  (void)in_sizes; (void)n_in; (void)out_size;
  static PFN_encodeTiled enc = nullptr;
  static void *pHT = nullptr, *pO = nullptr;
  if (!enc) {
    void* fn = nullptr;
    cudaDriverEntryPointQueryResult qr;
    if (cudaGetDriverEntryPoint("cuTensorMapEncodeTiled", &fn, cudaEnableDefault, &qr) != cudaSuccess || !fn) return;
    enc = (PFN_encodeTiled)fn;
    cudaFuncSetAttribute(fused_kernel, cudaFuncAttributeMaxDynamicSharedMemorySize, SMEM_BYTES);
    cudaGetSymbolAddress(&pHT, g_HT);
    cudaGetSymbolAddress(&pO, g_O);
  }
  Params prm;
  bool ok = true;
  {
    const uint64_t dims[5] = {1024, 2, 4, 16, 16}, str[4] = {2048, 65536, 4096, 262144};
    const uint32_t box[5] = {64, 2, 4, 16, 1};
    ok &= make_tm(enc, &prm.tmXB, d_in[4], 5, dims, str, box, CU_TENSOR_MAP_SWIZZLE_128B);
  }
  ok &= make_tm2(enc, &prm.tmBre, d_in[7], 1024, 1024, 64, 64);
  ok &= make_tm2(enc, &prm.tmBim, d_in[8], 1024, 1024, 64, 64);
  ok &= make_tm2(enc, &prm.tmXA, d_in[0], 1024, 2048, 64, 128);
  ok &= make_tm2(enc, &prm.tmWqkv, d_in[1], 3072, 1024, 64, 64);
  ok &= make_tm2(enc, &prm.tmWphi, d_in[2], 32, 1024, 32, 64, CU_TENSOR_MAP_SWIZZLE_64B);
  {
    const uint64_t dims[3] = {64, 2048, 32}, str[2] = {4096, 128};
    const uint32_t box[3] = {64, 64, 2};
    ok &= make_tm(enc, &prm.tmHT, pHT, 3, dims, str, box, CU_TENSOR_MAP_SWIZZLE_128B);
  }
  {
    const uint64_t dims[3] = {64, 2048, 32}, str[2] = {4096, 128};
    const uint32_t box[3] = {64, 16, 1};
    ok &= make_tm(enc, &prm.tmHTs, pHT, 3, dims, str, box, CU_TENSOR_MAP_SWIZZLE_128B);
  }
  ok &= make_tm2(enc, &prm.tmCre, d_in[9], 1024, 1024, 64, 64);
  ok &= make_tm2(enc, &prm.tmCim, d_in[10], 1024, 1024, 64, 64);
  ok &= make_tm2(enc, &prm.tmO, pO, 1024, 2048, 64, 128);
  ok &= make_tm2(enc, &prm.tmWo, d_in[3], 1024, 1024, 64, 64);
  if (!ok) return;
  prm.xB = (const __nv_bfloat16*)d_in[4];
  prm.lam_re = (const __nv_bfloat16*)d_in[5];
  prm.lam_im = (const __nv_bfloat16*)d_in[6];
  prm.log_dt = (const __nv_bfloat16*)d_in[11];
  prm.dskip = (const __nv_bfloat16*)d_in[12];
  prm.out = (float*)d_out;

  cudaLaunchConfig_t cfg = {};
  cfg.gridDim = dim3(128);
  cfg.blockDim = dim3(384);
  cfg.dynamicSmemBytes = SMEM_BYTES;
  cfg.stream = cudaStreamPerThread;
  cudaLaunchAttribute attr[1];
  attr[0].id = cudaLaunchAttributeClusterDimension;
  attr[0].val.clusterDim.x = 2; attr[0].val.clusterDim.y = 1; attr[0].val.clusterDim.z = 1;
  cfg.attrs = attr;
  cfg.numAttrs = 1;
  cudaLaunchKernelEx(&cfg, fused_kernel, prm);
}
```

```cpp
#include <cuda_runtime.h>
#include <cuda_bf16.h>
#include <cuda.h>
#include <stdint.h>
#include <type_traits>

namespace {

constexpr int SEQ = 2048;
constexpr int DM = 1024;
constexpr int STAGES = 5;
constexpr int STAGE_BYTES = 32768;
constexpr int OFF_EB = STAGES * STAGE_BYTES;
constexpr int OFF_PHI = OFF_EB;
constexpr int OFF_V = OFF_EB + 32768;
constexpr int OFF_WPHI = OFF_EB + 53248;
constexpr int OFF_ONES = OFF_EB + 61440;
constexpr int OFF_BAR = OFF_EB + 62464;
constexpr int SMEM_BYTES = OFF_BAR + 512 + 1024;
constexpr int B_EMPTY = 64, B_ORD = 128  , B_WPHI = 144, B_EPOCH = 152, B_PARAM = 160, B_KVX = 168  , B_EBA = 184  ,
              B_EPOCHV = 200, B_DEAD = 204, B_JOB = 208  , B_EBF = 256  ;

constexpr int KVW = 40;

struct Params {
  CUtensorMap tmXB;
  CUtensorMap tmBre, tmBim;
  CUtensorMap tmXA;
  CUtensorMap tmWqkv;
  CUtensorMap tmWphi;
  CUtensorMap tmHT;
  CUtensorMap tmHTs;
  CUtensorMap tmCre, tmCim;
  CUtensorMap tmO;
  CUtensorMap tmWo;
  const __nv_bfloat16* xB;
  const __nv_bfloat16* lam_re;
  const __nv_bfloat16* lam_im;
  const __nv_bfloat16* log_dt;
  const __nv_bfloat16* dskip;
  float* out;
};

__device__ __nv_bfloat16 g_HT[2048 * 2048];
__device__ __nv_bfloat16 g_O[SEQ * DM];
__device__ float g_kv[32 * 64 * KVW];
__device__ uint4 g_E[16 * 16 * 64];
struct Flags {
  unsigned ticket;   unsigned pad0[31];
  unsigned zero_cnt; unsigned pad1[31];
  unsigned hcnt[16 * 8];
  unsigned kvcnt[16 * 8];
  unsigned ocnt[2 * 16 * 8];
};
__device__ Flags g_flags;

__device__ __forceinline__ uint32_t smem_u32(const void* p) { return (uint32_t)__cvta_generic_to_shared(p); }
__device__ __forceinline__ void mbar_init(uint32_t bar, uint32_t count) {
  asm volatile("mbarrier.init.shared::cta.b64 [%0], %1;" ::"r"(bar), "r"(count));
}
__device__ __forceinline__ void mbar_expect_tx(uint32_t bar, uint32_t bytes) {
  asm volatile("mbarrier.arrive.expect_tx.shared::cta.b64 _, [%0], %1;" ::"r"(bar), "r"(bytes) : "memory");
}
__device__ __forceinline__ void mbar_arrive(uint32_t bar) {
  asm volatile("mbarrier.arrive.shared::cta.b64 _, [%0];" ::"r"(bar) : "memory");
}
__device__ __forceinline__ void mbar_arrive_cluster(uint32_t bar, uint32_t cta) {
  asm volatile("{\n.reg .b32 ra;\nmapa.shared::cluster.u32 ra, %0, %1;\nmbarrier.arrive.shared::cluster.b64 _, [ra];\n}" ::"r"(bar), "r"(cta) : "memory");
}
__device__ __forceinline__ uint32_t dead_addr(uint32_t bar) { return (bar & ~0x1FFu) + B_DEAD; }
__device__ __forceinline__ void mbar_wait(uint32_t bar, uint32_t parity) {
  asm volatile(
      "{\n.reg .pred p;\n.reg .u32 c, d;\n"
      "mov.u32 c, 0;\n"
      "WAIT_LOOP:\n"
      "mbarrier.try_wait.parity.shared::cta.b64 p, [%0], %1;\n"
      "@p bra WAIT_DONE;\n"
      "add.u32 c, c, 1;\n"
      "setp.gt.u32 p, c, 0x200000;\n"
      "@p st.volatile.shared.u32 [%2], c;\n"
      "ld.volatile.shared.u32 d, [%2];\n"
      "setp.eq.u32 p, d, 0;\n"
      "@p bra WAIT_LOOP;\n"
      "WAIT_DONE:\n}\n" ::"r"(bar), "r"(parity), "r"(dead_addr(bar)) : "memory");
}
__device__ __forceinline__ void mbar_wait_long(uint32_t bar, uint32_t parity) {
  asm volatile(
      "{\n.reg .pred p;\n.reg .u32 c, d;\n"
      "mov.u32 c, 0;\n"
      "WAITL_LOOP:\n"
      "mbarrier.try_wait.parity.shared::cta.b64 p, [%0], %1;\n"
      "@p bra WAITL_DONE;\n"
      "nanosleep.u32 100;\n"
      "add.u32 c, c, 1;\n"
      "setp.gt.u32 p, c, 0x200000;\n"
      "@p st.volatile.shared.u32 [%2], c;\n"
      "ld.volatile.shared.u32 d, [%2];\n"
      "setp.eq.u32 p, d, 0;\n"
      "@p bra WAITL_LOOP;\n"
      "WAITL_DONE:\n}\n" ::"r"(bar), "r"(parity), "r"(dead_addr(bar)) : "memory");
}
__device__ __forceinline__ bool give_up(uint32_t bars, unsigned spins) {
  unsigned d;
  if (spins > (1u << 20)) asm volatile("st.volatile.shared.u32 [%0], %1;" ::"r"(bars + B_DEAD), "r"(spins) : "memory");
  asm volatile("ld.volatile.shared.u32 %0, [%1];" : "=r"(d) : "r"(bars + B_DEAD) : "memory");
  return d != 0;
}
__device__ __forceinline__ unsigned ld_relaxed(const unsigned* p) {
  unsigned v;
  asm volatile("ld.relaxed.gpu.global.u32 %0, [%1];" : "=r"(v) : "l"(p) : "memory");
  return v;
}
__device__ __forceinline__ void wait_ge(uint32_t bars, const unsigned* p, unsigned target) {
  unsigned spins = 0;
  while ((int)(ld_relaxed(p) - target) < 0) {
    __nanosleep(128);
    if (give_up(bars, ++spins)) break;
  }
  asm volatile("{\n.reg .u32 v;\nld.acquire.gpu.global.u32 v, [%0];\n}" ::"l"(p) : "memory");
}
__device__ __forceinline__ void red_release_add(unsigned* p, unsigned v) {
  asm volatile("red.release.gpu.global.add.u32 [%0], %1;" ::"l"(p), "r"(v) : "memory");
}
__device__ __forceinline__ void red_relaxed_add(unsigned* p, unsigned v) {
  asm volatile("red.relaxed.gpu.global.add.u32 [%0], %1;" ::"l"(p), "r"(v) : "memory");
}
__device__ __forceinline__ void st_tagged(uint4* p, float a, float b, unsigned tag) {
  const unsigned long long w0 = ((unsigned long long)tag << 32) | __float_as_uint(a);
  const unsigned long long w1 = ((unsigned long long)tag << 32) | __float_as_uint(b);
  asm volatile("st.relaxed.gpu.global.v2.b64 [%0], {%1, %2};" ::"l"(p), "l"(w0), "l"(w1) : "memory");
}
__device__ __forceinline__ void bulk_commit() { asm volatile("cp.async.bulk.commit_group;" ::: "memory"); }
__device__ __forceinline__ void bulk_wait_read() { asm volatile("cp.async.bulk.wait_group.read 0;" ::: "memory"); }
__device__ __forceinline__ void bulk_wait_all() { asm volatile("cp.async.bulk.wait_group 0;" ::: "memory"); }
__device__ __forceinline__ void bulk_reduce_f32(float* dst, uint32_t src, uint32_t bytes) {
  asm volatile("cp.reduce.async.bulk.global.shared::cta.bulk_group.add.f32 [%0], [%1], %2;" ::"l"(dst), "r"(src), "r"(bytes) : "memory");
}
__device__ __forceinline__ void tma_store_3d(const CUtensorMap* tm, uint32_t src, int c0, int c1, int c2) {
  asm volatile("cp.async.bulk.tensor.3d.global.shared::cta.bulk_group [%0, {%2, %3, %4}], [%1];"
               ::"l"(tm), "r"(src), "r"(c0), "r"(c1), "r"(c2) : "memory");
}
__device__ __forceinline__ void fence_async_global() { asm volatile("fence.proxy.async.global;" ::: "memory"); }
__device__ __forceinline__ void fence_async_smem() { asm volatile("fence.proxy.async.shared::cta;" ::: "memory"); }
__device__ __forceinline__ void tma_2d(uint32_t dst, const CUtensorMap* tm, int c0, int c1, uint32_t bar) {
  asm volatile("cp.async.bulk.tensor.2d.shared::cluster.global.mbarrier::complete_tx::bytes [%0], [%1, {%3, %4}], [%2];"
               ::"r"(dst), "l"(tm), "r"(bar), "r"(c0), "r"(c1) : "memory");
}
__device__ __forceinline__ void tma_3d(uint32_t dst, const CUtensorMap* tm, int c0, int c1, int c2, uint32_t bar) {
  asm volatile("cp.async.bulk.tensor.3d.shared::cluster.global.mbarrier::complete_tx::bytes [%0], [%1, {%3, %4, %5}], [%2];"
               ::"r"(dst), "l"(tm), "r"(bar), "r"(c0), "r"(c1), "r"(c2) : "memory");
}
__device__ __forceinline__ void tma_4d(uint32_t dst, const CUtensorMap* tm, int c0, int c1, int c2, int c3, uint32_t bar) {
  asm volatile("cp.async.bulk.tensor.4d.shared::cluster.global.mbarrier::complete_tx::bytes [%0], [%1, {%3, %4, %5, %6}], [%2];"
               ::"r"(dst), "l"(tm), "r"(bar), "r"(c0), "r"(c1), "r"(c2), "r"(c3) : "memory");
}
__device__ __forceinline__ void tma_store_4d(const CUtensorMap* tm, uint32_t src, int c0, int c1, int c2, int c3) {
  asm volatile("cp.async.bulk.tensor.4d.global.shared::cta.bulk_group [%0, {%2, %3, %4, %5}], [%1];"
               ::"l"(tm), "r"(src), "r"(c0), "r"(c1), "r"(c2), "r"(c3) : "memory");
}
__device__ __forceinline__ void tma_5d(uint32_t dst, const CUtensorMap* tm, int c0, int c1, int c2, int c3, int c4, uint32_t bar) {
  asm volatile("cp.async.bulk.tensor.5d.shared::cluster.global.mbarrier::complete_tx::bytes [%0], [%1, {%3, %4, %5, %6, %7}], [%2];"
               ::"r"(dst), "l"(tm), "r"(bar), "r"(c0), "r"(c1), "r"(c2), "r"(c3), "r"(c4) : "memory");
}
__device__ __forceinline__ void tma_2d_mc(uint32_t dst, const CUtensorMap* tm, int c0, int c1, uint32_t bar) {
  asm volatile("cp.async.bulk.tensor.2d.shared::cluster.global.mbarrier::complete_tx::bytes.multicast::cluster [%0], [%1, {%3, %4}], [%2], %5;"
               ::"r"(dst), "l"(tm), "r"(bar), "r"(c0), "r"(c1), "h"((uint16_t)3) : "memory");
}
__device__ __forceinline__ bool elect_one() {
  uint32_t p;
  asm volatile("{\n.reg .pred e;\nelect.sync _|e, 0xffffffff;\nselp.u32 %0, 1, 0, e;\n}" : "=r"(p));
  return p != 0;
}
__device__ __forceinline__ void prefetch_tm(const CUtensorMap* tm) {
  asm volatile("prefetch.tensormap [%0];" ::"l"(tm) : "memory");
}
__device__ __forceinline__ void wgmma_fence() { asm volatile("wgmma.fence.sync.aligned;" ::: "memory"); }
__device__ __forceinline__ void wgmma_commit() { asm volatile("wgmma.commit_group.sync.aligned;" ::: "memory"); }
template <int N> __device__ __forceinline__ void wgmma_wait() { asm volatile("wgmma.wait_group.sync.aligned %0;" ::"n"(N) : "memory"); }
__device__ __forceinline__ void wg_bar(int id) {
  if (id == 1) asm volatile("bar.sync 1, 128;" ::: "memory");
  else asm volatile("bar.sync 2, 128;" ::: "memory");
}
template <int R> __device__ __forceinline__ void reg_alloc() { asm volatile("setmaxnreg.inc.sync.aligned.u32 %0;" ::"n"(R)); }
template <int R> __device__ __forceinline__ void reg_dealloc() { asm volatile("setmaxnreg.dec.sync.aligned.u32 %0;" ::"n"(R)); }

__device__ __forceinline__ uint64_t make_desc(uint32_t saddr, uint32_t lbo_bytes, uint32_t sbo_bytes, uint32_t layout) {
  uint64_t d = (uint64_t)((saddr & 0x3FFFF) >> 4);
  d |= (uint64_t)((lbo_bytes & 0x3FFFF) >> 4) << 16;
  d |= (uint64_t)((sbo_bytes & 0x3FFFF) >> 4) << 32;
  d |= (uint64_t)layout << 62;
  return d;
}
__device__ __forceinline__ uint64_t desc128(uint32_t lo) { return ((uint64_t)0x40000040u << 32) | lo; }
__device__ __forceinline__ uint32_t pack_bf16(float lo, float hi) {
  uint32_t r;
  asm("cvt.rn.bf16x2.f32 %0, %1, %2;" : "=r"(r) : "f"(hi), "f"(lo));
  return r;
}
__device__ __forceinline__ float ex2(float x) { float y; asm("ex2.approx.ftz.f32 %0, %1;" : "=f"(y) : "f"(x)); return y; }
__device__ __forceinline__ float rcp(float x) { float y; asm("rcp.approx.ftz.f32 %0, %1;" : "=f"(y) : "f"(x)); return y; }
__device__ __forceinline__ void stmatrix_x4(uint32_t addr, uint32_t r0, uint32_t r1, uint32_t r2, uint32_t r3) {
  asm volatile("stmatrix.sync.aligned.m8n8.x4.shared.b16 [%0], {%1, %2, %3, %4};" ::"r"(addr), "r"(r0), "r"(r1), "r"(r2), "r"(r3) : "memory");
}
template <int N> __device__ __forceinline__ void fence_regs(float (&d)[N]) {
#pragma unroll
  for (int i = 0; i < N; i++) asm volatile("" : "+f"(d[i])::"memory");
}

template <int TA, int TB>
__device__ __forceinline__ void wgmma_m64n128k16_ss(float (&d)[64], uint64_t descA, uint64_t descB) {
  asm volatile("{\n.reg .pred p;\nsetp.ne.b32 p, 1, 0;\n"
    "wgmma.mma_async.sync.aligned.m64n128k16.f32.bf16.bf16 "
    "{%0, %1, %2, %3, %4, %5, %6, %7, %8, %9, %10, %11, %12, %13, %14, %15, %16, %17, %18, %19, %20, %21, %22, %23, %24, %25, %26, %27, %28, %29, %30, %31, %32, %33, %34, %35, %36, %37, %38, %39, %40, %41, %42, %43, %44, %45, %46, %47, %48, %49, %50, %51, %52, %53, %54, %55, %56, %57, %58, %59, %60, %61, %62, %63}, "
    "%64, %65, p, 1, 1, %66, %67;\n}\n"
    : "+f"(d[0]), "+f"(d[1]), "+f"(d[2]), "+f"(d[3]), "+f"(d[4]), "+f"(d[5]), "+f"(d[6]), "+f"(d[7]), "+f"(d[8]), "+f"(d[9]), "+f"(d[10]), "+f"(d[11]), "+f"(d[12]), "+f"(d[13]), "+f"(d[14]), "+f"(d[15]), "+f"(d[16]), "+f"(d[17]), "+f"(d[18]), "+f"(d[19]), "+f"(d[20]), "+f"(d[21]), "+f"(d[22]), "+f"(d[23]), "+f"(d[24]), "+f"(d[25]), "+f"(d[26]), "+f"(d[27]), "+f"(d[28]), "+f"(d[29]), "+f"(d[30]), "+f"(d[31]), "+f"(d[32]), "+f"(d[33]), "+f"(d[34]), "+f"(d[35]), "+f"(d[36]), "+f"(d[37]), "+f"(d[38]), "+f"(d[39]), "+f"(d[40]), "+f"(d[41]), "+f"(d[42]), "+f"(d[43]), "+f"(d[44]), "+f"(d[45]), "+f"(d[46]), "+f"(d[47]), "+f"(d[48]), "+f"(d[49]), "+f"(d[50]), "+f"(d[51]), "+f"(d[52]), "+f"(d[53]), "+f"(d[54]), "+f"(d[55]), "+f"(d[56]), "+f"(d[57]), "+f"(d[58]), "+f"(d[59]), "+f"(d[60]), "+f"(d[61]), "+f"(d[62]), "+f"(d[63])
    : "l"(descA), "l"(descB), "n"(TA), "n"(TB));
}

template <int TA, int TB>
__device__ __forceinline__ void wgmma_m64n32k16_ss(float (&d)[16], uint64_t descA, uint64_t descB) {
  asm volatile("{\n.reg .pred p;\nsetp.ne.b32 p, 1, 0;\n"
    "wgmma.mma_async.sync.aligned.m64n32k16.f32.bf16.bf16 "
    "{%0, %1, %2, %3, %4, %5, %6, %7, %8, %9, %10, %11, %12, %13, %14, %15}, "
    "%16, %17, p, 1, 1, %18, %19;\n}\n"
    : "+f"(d[0]), "+f"(d[1]), "+f"(d[2]), "+f"(d[3]), "+f"(d[4]), "+f"(d[5]), "+f"(d[6]), "+f"(d[7]), "+f"(d[8]), "+f"(d[9]), "+f"(d[10]), "+f"(d[11]), "+f"(d[12]), "+f"(d[13]), "+f"(d[14]), "+f"(d[15])
    : "l"(descA), "l"(descB), "n"(TA), "n"(TB));
}

template <int TA, int TB>
__device__ __forceinline__ void wgmma_m64n32k16_ss_init(float (&d)[16], uint64_t descA, uint64_t descB) {
  asm volatile("{\n.reg .pred p;\nsetp.ne.b32 p, 0, 0;\n"
    "wgmma.mma_async.sync.aligned.m64n32k16.f32.bf16.bf16 "
    "{%0, %1, %2, %3, %4, %5, %6, %7, %8, %9, %10, %11, %12, %13, %14, %15}, "
    "%16, %17, p, 1, 1, %18, %19;\n}\n"
    : "=f"(d[0]), "=f"(d[1]), "=f"(d[2]), "=f"(d[3]), "=f"(d[4]), "=f"(d[5]), "=f"(d[6]), "=f"(d[7]), "=f"(d[8]), "=f"(d[9]), "=f"(d[10]), "=f"(d[11]), "=f"(d[12]), "=f"(d[13]), "=f"(d[14]), "=f"(d[15])
    : "l"(descA), "l"(descB), "n"(TA), "n"(TB));
}

template <int TB>
__device__ __forceinline__ void wgmma_m64n32k16_rs(float (&d)[16], uint32_t a0, uint32_t a1, uint32_t a2, uint32_t a3, uint64_t descB) {
  asm volatile("{\n.reg .pred p;\nsetp.ne.b32 p, 1, 0;\n"
    "wgmma.mma_async.sync.aligned.m64n32k16.f32.bf16.bf16 "
    "{%0, %1, %2, %3, %4, %5, %6, %7, %8, %9, %10, %11, %12, %13, %14, %15}, "
    "{%16, %17, %18, %19}, %20, p, 1, 1, %21;\n}\n"
    : "+f"(d[0]), "+f"(d[1]), "+f"(d[2]), "+f"(d[3]), "+f"(d[4]), "+f"(d[5]), "+f"(d[6]), "+f"(d[7]), "+f"(d[8]), "+f"(d[9]), "+f"(d[10]), "+f"(d[11]), "+f"(d[12]), "+f"(d[13]), "+f"(d[14]), "+f"(d[15])
    : "r"(a0), "r"(a1), "r"(a2), "r"(a3), "l"(descB), "n"(TB));
}

template <int TB>
__device__ __forceinline__ void wgmma_m64n32k16_rs_init(float (&d)[16], uint32_t a0, uint32_t a1, uint32_t a2, uint32_t a3, uint64_t descB) {
  asm volatile("{\n.reg .pred p;\nsetp.ne.b32 p, 0, 0;\n"
    "wgmma.mma_async.sync.aligned.m64n32k16.f32.bf16.bf16 "
    "{%0, %1, %2, %3, %4, %5, %6, %7, %8, %9, %10, %11, %12, %13, %14, %15}, "
    "{%16, %17, %18, %19}, %20, p, 1, 1, %21;\n}\n"
    : "=f"(d[0]), "=f"(d[1]), "=f"(d[2]), "=f"(d[3]), "=f"(d[4]), "=f"(d[5]), "=f"(d[6]), "=f"(d[7]), "=f"(d[8]), "=f"(d[9]), "=f"(d[10]), "=f"(d[11]), "=f"(d[12]), "=f"(d[13]), "=f"(d[14]), "=f"(d[15])
    : "r"(a0), "r"(a1), "r"(a2), "r"(a3), "l"(descB), "n"(TB));
}

template <int TA, int TB>
__device__ __forceinline__ void wgmma_m64n40k16_ss(float (&d)[20], uint64_t descA, uint64_t descB) {
  asm volatile("{\n.reg .pred p;\nsetp.ne.b32 p, 1, 0;\n"
    "wgmma.mma_async.sync.aligned.m64n40k16.f32.bf16.bf16 "
    "{%0, %1, %2, %3, %4, %5, %6, %7, %8, %9, %10, %11, %12, %13, %14, %15, %16, %17, %18, %19}, "
    "%20, %21, p, 1, 1, %22, %23;\n}\n"
    : "+f"(d[0]), "+f"(d[1]), "+f"(d[2]), "+f"(d[3]), "+f"(d[4]), "+f"(d[5]), "+f"(d[6]), "+f"(d[7]), "+f"(d[8]), "+f"(d[9]), "+f"(d[10]), "+f"(d[11]), "+f"(d[12]), "+f"(d[13]), "+f"(d[14]), "+f"(d[15]), "+f"(d[16]), "+f"(d[17]), "+f"(d[18]), "+f"(d[19])
    : "l"(descA), "l"(descB), "n"(TA), "n"(TB));
}

template <int TA, int TB>
__device__ __forceinline__ void wgmma_m64n40k16_ss_init(float (&d)[20], uint64_t descA, uint64_t descB) {
  asm volatile("{\n.reg .pred p;\nsetp.ne.b32 p, 0, 0;\n"
    "wgmma.mma_async.sync.aligned.m64n40k16.f32.bf16.bf16 "
    "{%0, %1, %2, %3, %4, %5, %6, %7, %8, %9, %10, %11, %12, %13, %14, %15, %16, %17, %18, %19}, "
    "%20, %21, p, 1, 1, %22, %23;\n}\n"
    : "=f"(d[0]), "=f"(d[1]), "=f"(d[2]), "=f"(d[3]), "=f"(d[4]), "=f"(d[5]), "=f"(d[6]), "=f"(d[7]), "=f"(d[8]), "=f"(d[9]), "=f"(d[10]), "=f"(d[11]), "=f"(d[12]), "=f"(d[13]), "=f"(d[14]), "=f"(d[15]), "=f"(d[16]), "=f"(d[17]), "=f"(d[18]), "=f"(d[19])
    : "l"(descA), "l"(descB), "n"(TA), "n"(TB));
}

template <int TB>
__device__ __forceinline__ void wgmma_m64n40k16_rs(float (&d)[20], uint32_t a0, uint32_t a1, uint32_t a2, uint32_t a3, uint64_t descB) {
  asm volatile("{\n.reg .pred p;\nsetp.ne.b32 p, 1, 0;\n"
    "wgmma.mma_async.sync.aligned.m64n40k16.f32.bf16.bf16 "
    "{%0, %1, %2, %3, %4, %5, %6, %7, %8, %9, %10, %11, %12, %13, %14, %15, %16, %17, %18, %19}, "
    "{%20, %21, %22, %23}, %24, p, 1, 1, %25;\n}\n"
    : "+f"(d[0]), "+f"(d[1]), "+f"(d[2]), "+f"(d[3]), "+f"(d[4]), "+f"(d[5]), "+f"(d[6]), "+f"(d[7]), "+f"(d[8]), "+f"(d[9]), "+f"(d[10]), "+f"(d[11]), "+f"(d[12]), "+f"(d[13]), "+f"(d[14]), "+f"(d[15]), "+f"(d[16]), "+f"(d[17]), "+f"(d[18]), "+f"(d[19])
    : "r"(a0), "r"(a1), "r"(a2), "r"(a3), "l"(descB), "n"(TB));
}

template <int TB>
__device__ __forceinline__ void wgmma_m64n40k16_rs_init(float (&d)[20], uint32_t a0, uint32_t a1, uint32_t a2, uint32_t a3, uint64_t descB) {
  asm volatile("{\n.reg .pred p;\nsetp.ne.b32 p, 0, 0;\n"
    "wgmma.mma_async.sync.aligned.m64n40k16.f32.bf16.bf16 "
    "{%0, %1, %2, %3, %4, %5, %6, %7, %8, %9, %10, %11, %12, %13, %14, %15, %16, %17, %18, %19}, "
    "{%20, %21, %22, %23}, %24, p, 1, 1, %25;\n}\n"
    : "=f"(d[0]), "=f"(d[1]), "=f"(d[2]), "=f"(d[3]), "=f"(d[4]), "=f"(d[5]), "=f"(d[6]), "=f"(d[7]), "=f"(d[8]), "=f"(d[9]), "=f"(d[10]), "=f"(d[11]), "=f"(d[12]), "=f"(d[13]), "=f"(d[14]), "=f"(d[15]), "=f"(d[16]), "=f"(d[17]), "=f"(d[18]), "=f"(d[19])
    : "r"(a0), "r"(a1), "r"(a2), "r"(a3), "l"(descB), "n"(TB));
}


template <int MODE>
__device__ __forceinline__ void mainloop(float (&acc0)[64], float (&acc1)[64], int it0, int nkb, uint32_t sbase, int cw,
                                         uint32_t ord_parity) {
  const uint32_t bars = sbase + OFF_BAR;
  const int lane = threadIdx.x & 31;
  int stage = it0 % STAGES;
  uint32_t phase = (it0 / STAGES) & 1;
#pragma unroll
  for (int i = 0; i < 64; i++) { acc0[i] = 0.f; acc1[i] = 0.f; }
  mbar_wait(bars + B_ORD + 8 * cw, ord_parity);
  int prev = 0;
  for (int kb = 0; kb < nkb; kb++) {
    mbar_wait(bars + 8 * stage, phase);
    const uint32_t lo = ((sbase & 0x3FFFFu) + stage * STAGE_BYTES) >> 4;
    const uint32_t loK = lo | (1u << 16), loM = lo | (512u << 16);
    wgmma_fence();
#pragma unroll
    for (int k = 0; k < 4; k++) {
      if (MODE == 0) {
        const uint64_t dx = desc128(loK + 1024 + 2 * k);
        wgmma_m64n128k16_ss<0, 0>(acc0, desc128(loK + 2 * k), dx);
        wgmma_m64n128k16_ss<0, 0>(acc1, desc128(loK + 512 + 2 * k), dx);
      } else if (MODE == 1) {
        const uint64_t dw = desc128(loM + 128 * k);
        wgmma_m64n128k16_ss<0, 1>(acc0, desc128(loK + 1024 + 2 * k), dw);
        wgmma_m64n128k16_ss<0, 1>(acc1, desc128(loK + 1536 + 2 * k), dw);
      } else {
        const uint64_t dw = desc128(loK + 2 * k);
        wgmma_m64n128k16_ss<1, 0>(acc0, desc128(loM + 1024 + 128 * k), dw);
        wgmma_m64n128k16_ss<1, 0>(acc1, desc128(loM + 1536 + 128 * k), dw);
      }
      if (k == 1 && kb == nkb - 1 && (threadIdx.x & 127) == 0) mbar_arrive(bars + B_ORD + 8 * (cw ^ 1));
    }
    wgmma_commit();
    wgmma_wait<1>();
    if (kb > 0 && lane < 2) mbar_arrive_cluster(bars + B_EMPTY + 8 * prev, lane);
    prev = stage;
    if (++stage == STAGES) { stage = 0; phase ^= 1; }
  }
  wgmma_wait<0>();
  if (lane < 2) mbar_arrive_cluster(bars + B_EMPTY + 8 * prev, lane);
  fence_regs(acc0);
  fence_regs(acc1);
}

template <int N>
__device__ __forceinline__ void dual_softmax_n(const float (&p)[N][16], uint32_t (&pos)[N][8], uint32_t (&neg)[N][8]) {
  constexpr float L2E = 1.4426950408889634f;
  float ca[N][2], cb[N][2];
  {
    float mx[N][2], mn[N][2];
#pragma unroll
    for (int i = 0; i < N; i++)
#pragma unroll
      for (int r = 0; r < 2; r++) {
        const int o = 2 * r;
        mx[i][r] = fmaxf(fmaxf(fmaxf(p[i][o], p[i][o + 1]), fmaxf(p[i][4 + o], p[i][5 + o])),
                         fmaxf(fmaxf(p[i][8 + o], p[i][9 + o]), fmaxf(p[i][12 + o], p[i][13 + o])));
        mn[i][r] = fminf(fminf(fminf(p[i][o], p[i][o + 1]), fminf(p[i][4 + o], p[i][5 + o])),
                         fminf(fminf(p[i][8 + o], p[i][9 + o]), fminf(p[i][12 + o], p[i][13 + o])));
      }
#pragma unroll
    for (int o = 1; o <= 2; o <<= 1) {
      float tx[N][2], tn[N][2];
#pragma unroll
      for (int i = 0; i < N; i++)
#pragma unroll
        for (int r = 0; r < 2; r++) { tx[i][r] = __shfl_xor_sync(0xffffffffu, mx[i][r], o); tn[i][r] = __shfl_xor_sync(0xffffffffu, mn[i][r], o); }
#pragma unroll
      for (int i = 0; i < N; i++)
#pragma unroll
        for (int r = 0; r < 2; r++) { mx[i][r] = fmaxf(mx[i][r], tx[i][r]); mn[i][r] = fminf(mn[i][r], tn[i][r]); }
    }
#pragma unroll
    for (int i = 0; i < N; i++)
#pragma unroll
      for (int r = 0; r < 2; r++) { ca[i][r] = -mx[i][r] * L2E; cb[i][r] = mn[i][r] * L2E; }
  }
  float ep[2][16], en[2][16];
  float rp[2], rn[2];
#pragma unroll
  for (int i = 0; i <= N; i++) {
    const int cur = i & 1, prv = cur ^ 1;
    if (i > 0) {
      float sp[2], sn[2];
#pragma unroll
      for (int r = 0; r < 2; r++) {
        const int o = 2 * r;
        sp[r] = ((ep[prv][o] + ep[prv][o + 1]) + (ep[prv][4 + o] + ep[prv][5 + o])) + ((ep[prv][8 + o] + ep[prv][9 + o]) + (ep[prv][12 + o] + ep[prv][13 + o]));
        sn[r] = ((en[prv][o] + en[prv][o + 1]) + (en[prv][4 + o] + en[prv][5 + o])) + ((en[prv][8 + o] + en[prv][9 + o]) + (en[prv][12 + o] + en[prv][13 + o]));
      }
      float t0[2], t1[2];
#pragma unroll
      for (int r = 0; r < 2; r++) { t0[r] = __shfl_xor_sync(0xffffffffu, sp[r], 1); t1[r] = __shfl_xor_sync(0xffffffffu, sn[r], 1); }
      if (i < N) {
#pragma unroll
        for (int e = 0; e < 4; e++) {
          ep[cur][e] = ex2(fmaf(p[i][e], L2E, ca[i][e >> 1])); en[cur][e] = ex2(fmaf(p[i][e], -L2E, cb[i][e >> 1]));
        }
      }
#pragma unroll
      for (int r = 0; r < 2; r++) { sp[r] += t0[r]; sn[r] += t1[r]; }
#pragma unroll
      for (int r = 0; r < 2; r++) { t0[r] = __shfl_xor_sync(0xffffffffu, sp[r], 2); t1[r] = __shfl_xor_sync(0xffffffffu, sn[r], 2); }
      if (i < N) {
#pragma unroll
        for (int e = 4; e < 8; e++) {
          ep[cur][e] = ex2(fmaf(p[i][e], L2E, ca[i][(e >> 1) & 1])); en[cur][e] = ex2(fmaf(p[i][e], -L2E, cb[i][(e >> 1) & 1]));
        }
      }
#pragma unroll
      for (int r = 0; r < 2; r++) { rp[r] = rcp(sp[r] + t0[r]); rn[r] = rcp(sn[r] + t1[r]); }
    } else {
#pragma unroll
      for (int e = 0; e < 8; e++) {
        ep[cur][e] = ex2(fmaf(p[i][e], L2E, ca[i][(e >> 1) & 1])); en[cur][e] = ex2(fmaf(p[i][e], -L2E, cb[i][(e >> 1) & 1]));
      }
    }
#pragma unroll
    for (int j = 0; j < 4; j++) {
      if (i < N && j >= 2) {
#pragma unroll
        for (int e = 4 * j; e < 4 * j + 4; e++) {
          ep[cur][e] = ex2(fmaf(p[i][e], L2E, ca[i][(e >> 1) & 1])); en[cur][e] = ex2(fmaf(p[i][e], -L2E, cb[i][(e >> 1) & 1]));
        }
      }
      if (i > 0) {
#pragma unroll
        for (int r = 0; r < 2; r++) {
          pos[i - 1][2 * j + r] = pack_bf16(ep[prv][4 * j + 2 * r] * rp[r], ep[prv][4 * j + 2 * r + 1] * rp[r]);
          neg[i - 1][2 * j + r] = pack_bf16(en[prv][4 * j + 2 * r] * rn[r], en[prv][4 * j + 2 * r + 1] * rn[r]);
        }
      }
    }
  }
}

__device__ __forceinline__ float4 lds128(uint32_t addr) {
  float4 v;
  asm volatile("ld.shared.v4.f32 {%0, %1, %2, %3}, [%4];" : "=f"(v.x), "=f"(v.y), "=f"(v.z), "=f"(v.w) : "r"(addr) : "memory");
  return v;
}
__device__ __forceinline__ float2 lds64(uint32_t addr) {
  float2 v;
  asm volatile("ld.shared.v2.f32 {%0, %1}, [%2];" : "=f"(v.x), "=f"(v.y) : "r"(addr) : "memory");
  return v;
}
__device__ __forceinline__ void sts128(uint32_t addr, float a, float b, float c, float d) {
  asm volatile("st.shared.v4.f32 [%0], {%1, %2, %3, %4};" ::"r"(addr), "f"(a), "f"(b), "f"(c), "f"(d) : "memory");
}
struct cplx { float r, i; };
__device__ __forceinline__ cplx cmul(cplx a, cplx b) { return {a.r * b.r - a.i * b.i, a.r * b.i + a.i * b.r}; }
__device__ __forceinline__ cplx cfma(cplx a, cplx b, cplx c) {
  return {fmaf(a.r, b.r, fmaf(-a.i, b.i, c.r)), fmaf(a.r, b.i, fmaf(a.i, b.r, c.i))};
}
__device__ __forceinline__ cplx shfl_up_c(cplx v, int d) {
  return {__shfl_up_sync(0xffffffffu, v.r, d, 4), __shfl_up_sync(0xffffffffu, v.i, d, 4)};
}

struct ChanParams { cplx lam, c2, l32, l64, l128, g32, f512; };
constexpr int PSTRIDE = 80;

__device__ __forceinline__ void chan_params(float lr, float li, float log_dt, uint32_t dst) {
  const float dt = __bfloat162float(__float2bfloat16(expf(log_dt)));
  const float mag = expf(dt * lr);
  float sn, cs;
  sincosf(dt * li, &sn, &cs);
  const cplx lam = {mag * cs, mag * sn};
  const float nr = lam.r - 1.0f, ni = lam.i;
  const float den = lr * lr + li * li;
  const cplx c2 = {2.0f * (nr * lr + ni * li) / den, 2.0f * (ni * lr - nr * li) / den};
  cplx l = lam;
#pragma unroll 1
  for (int s = 0; s < 5; s++) l = cmul(l, l);
  const cplx l32 = l, l64 = cmul(l32, l32), l96 = cmul(l64, l32), l128 = cmul(l64, l64);
  const cplx l256 = cmul(l128, l128), l512 = cmul(l256, l256), l1024 = cmul(l512, l512), l1536 = cmul(l1024, l512);
  sts128(dst, lam.r, lam.i, c2.r, c2.i);
  sts128(dst + 16, l32.r, l32.i, l64.r, l64.i);
  sts128(dst + 32, l96.r, l96.i, l128.r, l128.i);
  sts128(dst + 48, l512.r, l512.i, l1024.r, l1024.i);
  sts128(dst + 64, l1536.r, l1536.i, 1.0f, 0.0f);
}
__device__ __forceinline__ ChanParams load_params(uint32_t src, int q) {
  ChanParams c;
  const float4 a = lds128(src), b = lds128(src + 16), d = lds128(src + 32);
  c.lam = {a.x, a.y}; c.c2 = {a.z, a.w}; c.l32 = {b.x, b.y}; c.l64 = {b.z, b.w}; c.l128 = {d.z, d.w};
  const float2 g = lds64(src + (q == 0 ? 72 : 8 + 8 * q)), f = lds64(src + (q == 0 ? 72 : 40 + 8 * q));
  c.g32 = {g.x, g.y}; c.f512 = {f.x, f.y};
  return c;
}

__device__ __forceinline__ void epi_bu(float (&are)[64], float (&aim)[64], const ChanParams (&cp)[2],
                                       uint32_t sbase, int G, int chunk, int cw, unsigned epoch) {
  const int lane = threadIdx.x & 31, w = (threadIdx.x & 127) >> 5, q = lane & 3, r8 = lane >> 2;
  cplx E[2] = {{0.f, 0.f}, {0.f, 0.f}};
#pragma unroll
  for (int k8 = 0; k8 < 16; k8++)
#pragma unroll
    for (int e = 0; e < 2; e++)
#pragma unroll
      for (int c = 0; c < 2; c++) E[c] = cfma(cp[c].lam, E[c], cplx{are[4 * k8 + 2 * c + e], aim[4 * k8 + 2 * c + e]});
  cplx prev[2];
#pragma unroll
  for (int c = 0; c < 2; c++) {
    cplx t = shfl_up_c(E[c], 1);
    if (q >= 1) E[c] = cfma(cp[c].l32, t, E[c]);
    t = shfl_up_c(E[c], 2);
    if (q >= 2) E[c] = cfma(cp[c].l64, t, E[c]);
    prev[c] = shfl_up_c(E[c], 1);
    if (q == 0) prev[c] = {0.f, 0.f};
  }
  uint4* gE = g_E + (size_t)G * 16 * 64 + 16 * w + r8;
  if (q == 3) {
    st_tagged(gE + chunk * 64, E[0].r, E[0].i, epoch);
    st_tagged(gE + chunk * 64 + 8, E[1].r, E[1].i, epoch);
  }
  cplx V[2][4];
  {
    unsigned long long w0[8], w1[8];
    unsigned pending = 0;
#pragma unroll
    for (int i = 0; i < 8; i++) {
      w0[i] = 0ull; w1[i] = 0ull;
      if (chunk - 1 - 4 * q - (i & 3) >= 0) pending |= 1u << i;
    }
    unsigned spins = 0;
    if (chunk > 0) __nanosleep(1000);
    while (true) {
#pragma unroll
      for (int i = 0; i < 8; i++)
        asm volatile("{\n.reg .pred p;\nsetp.ne.u32 p, %3, 0;\n@p ld.relaxed.gpu.global.v2.b64 {%0, %1}, [%2];\n}"
                     : "+l"(w0[i]), "+l"(w1[i]) : "l"(gE + (chunk - 1 - 4 * q - (i & 3)) * 64 + 8 * (i >> 2)), "r"(pending & (1u << i)) : "memory");
#pragma unroll
      for (int i = 0; i < 8; i++)
        if ((unsigned)(w0[i] >> 32) == epoch && (unsigned)(w1[i] >> 32) == epoch) pending &= ~(1u << i);
      if (__all_sync(0xffffffffu, pending == 0)) break;
      __nanosleep(500);
      if (give_up(sbase + OFF_BAR, ++spins)) break;
    }
#pragma unroll
    for (int i = 0; i < 8; i++) V[i >> 2][i & 3] = {__uint_as_float((unsigned)w0[i]), __uint_as_float((unsigned)w1[i])};
  }
  cplx s[2];
#pragma unroll
  for (int c = 0; c < 2; c++) {
    cplx Pq = V[c][3];
#pragma unroll
    for (int jj = 2; jj >= 0; jj--) Pq = cfma(cp[c].l128, Pq, V[c][jj]);
    Pq = cmul(Pq, cp[c].f512);
#pragma unroll
    for (int o = 1; o <= 2; o <<= 1) {
      Pq.r += __shfl_xor_sync(0xffffffffu, Pq.r, o);
      Pq.i += __shfl_xor_sync(0xffffffffu, Pq.i, o);
    }
    s[c] = cfma(cp[c].g32, Pq, prev[c]);
  }
  if (cw == 1) mbar_wait(sbase + OFF_BAR + B_EBF, 0);
#pragma unroll
  for (int qq = 0; qq < 4; qq++) {
    uint32_t ore[2][4], oim[2][4];
#pragma unroll
    for (int kk = 0; kk < 4; kk++) {
      const int k8 = 4 * qq + kk;
      float hr[2][2], hi[2][2];
#pragma unroll
      for (int e = 0; e < 2; e++)
#pragma unroll
        for (int c = 0; c < 2; c++) {
          s[c] = cfma(cp[c].lam, s[c], cplx{are[4 * k8 + 2 * c + e], aim[4 * k8 + 2 * c + e]});
          hr[c][e] = fmaf(cp[c].c2.r, s[c].r, -cp[c].c2.i * s[c].i);
          hi[c][e] = -fmaf(cp[c].c2.r, s[c].i, cp[c].c2.i * s[c].r);
        }
#pragma unroll
      for (int c = 0; c < 2; c++) {
        ore[c][kk] = pack_bf16(hr[c][0], hr[c][1]);
        oim[c][kk] = pack_bf16(hi[c][0], hi[c][1]);
      }
    }
#pragma unroll
    for (int c = 0; c < 2; c++) {
      const int row = 16 * w + r8 + 8 * c;
      const uint32_t addr = sbase + OFF_PHI + (qq >> 1) * 8192 + row * 128 + ((((qq & 1) * 4 + q) ^ (row & 7)) << 4);
      asm volatile("st.shared.v4.b32 [%0], {%1, %2, %3, %4};" ::"r"(addr), "r"(ore[c][0]), "r"(ore[c][1]), "r"(ore[c][2]), "r"(ore[c][3]) : "memory");
      asm volatile("st.shared.v4.b32 [%0], {%1, %2, %3, %4};" ::"r"(addr + 32768), "r"(oim[c][0]), "r"(oim[c][1]), "r"(oim[c][2]), "r"(oim[c][3]) : "memory");
    }
  }
  fence_async_smem();
  wg_bar(1 + cw);
  if ((threadIdx.x & 127) == 0) mbar_arrive(sbase + OFF_BAR + B_JOB + 8 * cw);
}

__device__ __forceinline__ void q_issue_num(float (&num)[20], const uint32_t (&pos)[8], const uint32_t (&neg)[8], uint32_t b) {
  wgmma_fence();
  wgmma_m64n40k16_rs_init<1>(num, pos[0], pos[1], pos[2], pos[3], make_desc(b, 640, 128, 0));
  wgmma_m64n40k16_rs<1>(num, pos[4], pos[5], pos[6], pos[7], make_desc(b + 1280, 640, 128, 0));
  wgmma_m64n40k16_rs<1>(num, neg[0], neg[1], neg[2], neg[3], make_desc(b + 2560, 640, 128, 0));
  wgmma_m64n40k16_rs<1>(num, neg[4], neg[5], neg[6], neg[7], make_desc(b + 3840, 640, 128, 0));
  wgmma_commit();
}
__device__ __forceinline__ void q_store_o(const float (&num)[20], uint32_t rowaddr, int chunk0) {
  const int lane = threadIdx.x & 31, mi = lane >> 3, rin = lane & 7;
  const float d0 = __shfl_sync(0xffffffffu, num[16], lane & ~3), d1 = __shfl_sync(0xffffffffu, num[18], lane & ~3);
  const float i0 = __fdividef(1.0f, d0 + 1e-6f), i1 = __fdividef(1.0f, d1 + 1e-6f);
#pragma unroll
  for (int jp = 0; jp < 2; jp++) {
    const int c0 = chunk0 + jp * 2 + (mi >> 1);
    stmatrix_x4(rowaddr + ((c0 ^ rin) << 4), pack_bf16(num[8 * jp] * i0, num[8 * jp + 1] * i0),
                pack_bf16(num[8 * jp + 2] * i1, num[8 * jp + 3] * i1), pack_bf16(num[8 * jp + 4] * i0, num[8 * jp + 5] * i0),
                pack_bf16(num[8 * jp + 6] * i1, num[8 * jp + 7] * i1));
  }
}
__device__ __forceinline__ void epi_attn(float (&acc0)[64], float (&acc1)[64], uint32_t sbase, int cw, bool isq) {
  const int t = threadIdx.x & 127, lane = t & 31, w = t >> 5, q = lane & 3, r8 = lane >> 2;
  const int mi = lane >> 3, rin = lane & 7;
  const int row0 = w * 16 + (mi & 1) * 8 + rin;
  uint32_t kf[2][16];
  if (isq) {
#pragma unroll
    for (int j = 0; j < 16; j += 2) {
      const uint32_t addr = sbase + OFF_PHI + (j >> 3) * 16384 + row0 * 128 + ((((j & 7) + (mi >> 1)) ^ rin) << 4);
      stmatrix_x4(addr, pack_bf16(acc0[4 * j], acc0[4 * j + 1]), pack_bf16(acc0[4 * j + 2], acc0[4 * j + 3]),
                  pack_bf16(acc0[4 * j + 4], acc0[4 * j + 5]), pack_bf16(acc0[4 * j + 6], acc0[4 * j + 7]));
      stmatrix_x4(addr + 8192, pack_bf16(acc1[4 * j], acc1[4 * j + 1]), pack_bf16(acc1[4 * j + 2], acc1[4 * j + 3]),
                  pack_bf16(acc1[4 * j + 4], acc1[4 * j + 5]), pack_bf16(acc1[4 * j + 6], acc1[4 * j + 7]));
    }
#pragma unroll
    for (int i = 0; i < 16; i++) { kf[0][i] = 0; kf[1][i] = 0; }
  } else {
#pragma unroll
    for (int j = 8; j < 16; j += 2) {
      const uint32_t addr = sbase + OFF_PHI + 16384 + ((j - 8) >> 2) * 8192 + row0 * 64 + ((((j & 3) + (mi >> 1)) ^ ((row0 >> 1) & 3)) << 4);
      stmatrix_x4(addr, pack_bf16(acc0[4 * j], acc0[4 * j + 1]), pack_bf16(acc0[4 * j + 2], acc0[4 * j + 3]),
                  pack_bf16(acc0[4 * j + 4], acc0[4 * j + 5]), pack_bf16(acc0[4 * j + 6], acc0[4 * j + 7]));
      stmatrix_x4(addr + 4096, pack_bf16(acc1[4 * j], acc1[4 * j + 1]), pack_bf16(acc1[4 * j + 2], acc1[4 * j + 3]),
                  pack_bf16(acc1[4 * j + 4], acc1[4 * j + 5]), pack_bf16(acc1[4 * j + 6], acc1[4 * j + 7]));
    }
#pragma unroll
    for (int i = 0; i < 16; i++) {
      kf[0][i] = pack_bf16(acc0[2 * i], acc0[2 * i + 1]);
      kf[1][i] = pack_bf16(acc1[2 * i], acc1[2 * i + 1]);
    }
  }
  fence_async_smem();
  wg_bar(1 + cw);
  const int nsub = isq ? 2 : 1;
#pragma unroll 1
  for (int sub = 0; sub < nsub; sub++) {
    const uint32_t tile = sbase + OFF_PHI + sub * 16384;
    const uint32_t wp = sbase + OFF_WPHI + (isq ? 2 * sub : 2 * cw) * 2048;
    float pq[4][16];
    uint32_t pos[4][8], neg[4][8];
    if (isq) {
      wgmma_fence();
#pragma unroll
      for (int i = 0; i < 4; i++) {
        const uint32_t a = tile + (i & 1) * 8192 + (i >> 1) * 64, b = wp + (i >> 1) * 2048;
        wgmma_m64n32k16_ss_init<0, 1>(pq[i], make_desc(a, 16, 1024, 1), make_desc(b, 512, 512, 2));
        wgmma_m64n32k16_ss<0, 1>(pq[i], make_desc(a + 32, 16, 1024, 1), make_desc(b + 1024, 512, 512, 2));
      }
    } else {
      wgmma_fence();
#pragma unroll
      for (int i = 0; i < 4; i++) {
        const uint32_t b = wp + (i >> 1) * 2048;
        const uint32_t* f = &kf[i & 1][8 * (i >> 1)];
        wgmma_m64n32k16_rs_init<1>(pq[i], f[0], f[1], f[2], f[3], make_desc(b, 512, 512, 2));
        wgmma_m64n32k16_rs<1>(pq[i], f[4], f[5], f[6], f[7], make_desc(b + 1024, 512, 512, 2));
      }
    }
    wgmma_commit();
    wgmma_wait<0>();
#pragma unroll
    for (int i = 0; i < 4; i++) fence_regs(pq[i]);
    dual_softmax_n<4>(pq, pos, neg);
    if (!isq) {
      float kvacc[2][20];
      mbar_wait(sbase + OFF_BAR + B_EBF + 8 + 8 * cw, 0);
#pragma unroll
      for (int hh = 0; hh < 2; hh++) {
#pragma unroll
        for (int half = 0; half < 2; half++) {
          const uint32_t rb = sbase + OFF_PHI + hh * 32768 + (half * 64 + row0) * 128;
#pragma unroll
          for (int jp = 0; jp < 2; jp++) {
            const int c0 = jp * 2 + (mi >> 1), i = 2 * hh + half;
            stmatrix_x4(rb + ((c0 ^ rin) << 4), pos[i][4 * jp], pos[i][4 * jp + 1], pos[i][4 * jp + 2], pos[i][4 * jp + 3]);
            stmatrix_x4(rb + (((c0 + 4) ^ rin) << 4), neg[i][4 * jp], neg[i][4 * jp + 1], neg[i][4 * jp + 2], neg[i][4 * jp + 3]);
          }
        }
      }
      fence_async_smem();
      wg_bar(1 + cw);
      wgmma_fence();
#pragma unroll
      for (int hh = 0; hh < 2; hh++)
#pragma unroll
        for (int ks = 0; ks < 8; ks++) {
          const uint32_t vb = sbase + OFF_PHI + 16384 + hh * 8192 + ks * 1024;
          const uint64_t da = make_desc(sbase + OFF_PHI + hh * 32768 + ks * 2048, 1024, 1024, 1);
          const uint64_t db = make_desc(vb, sbase + OFF_ONES - vb, 512, 2);
          if (ks == 0) wgmma_m64n40k16_ss_init<1, 1>(kvacc[hh], da, db);
          else wgmma_m64n40k16_ss<1, 1>(kvacc[hh], da, db);
        }
      wgmma_commit();
      wgmma_wait<0>();
      fence_regs(kvacc[0]);
      fence_regs(kvacc[1]);
      wg_bar(1 + cw);
      if (t == 0) mbar_arrive(sbase + OFF_BAR + B_EBA + 8 * cw);
#pragma unroll
      for (int hh = 0; hh < 2; hh++) {
        const uint32_t dst = sbase + OFF_V + hh * 10240 + ((16 * w + r8) * KVW + 2 * q) * 4;
#pragma unroll
        for (int j = 0; j < 5; j++) {
          asm volatile("st.shared.v2.f32 [%0], {%1, %2};" ::"r"(dst + 32 * j), "f"(kvacc[hh][4 * j]), "f"(kvacc[hh][4 * j + 1]) : "memory");
          asm volatile("st.shared.v2.f32 [%0], {%1, %2};" ::"r"(dst + 8 * KVW * 4 + 32 * j), "f"(kvacc[hh][4 * j + 2]), "f"(kvacc[hh][4 * j + 3]) : "memory");
        }
      }
      fence_async_smem();
      wg_bar(1 + cw);
      if (t == 0) mbar_arrive(sbase + OFF_BAR + B_JOB + 16 + 8 * cw);
    } else {
      float num[4][20];
      mbar_wait(sbase + OFF_BAR + B_KVX + 8 * sub, 0);
#pragma unroll
      for (int i = 0; i < 4; i++) q_issue_num(num[i], pos[i], neg[i], sbase + OFF_V + (2 * sub + (i >> 1)) * 5120);
      wgmma_wait<2>();
      fence_regs(num[0]); fence_regs(num[1]);
      q_store_o(num[0], tile + row0 * 128, 0);
      q_store_o(num[1], tile + 8192 + row0 * 128, 0);
      wgmma_wait<0>();
      fence_regs(num[2]); fence_regs(num[3]);
      q_store_o(num[2], tile + row0 * 128, 4);
      q_store_o(num[3], tile + 8192 + row0 * 128, 4);
      fence_async_smem();
      wg_bar(1);
      if (t == 0) mbar_arrive(sbase + OFF_BAR + B_JOB + 32 + 8 * sub);
    }
  }
}

__device__ __forceinline__ void helper_kv(uint32_t sbase, int g, unsigned epoch) {
  const int h = threadIdx.x - 64;
  mbar_wait_long(sbase + OFF_BAR + B_EBF + 24, 0);
#pragma unroll 1
  for (int pr = 0; pr < 2; pr++) {
    if ((h & 31) == 0) {
      wait_ge(sbase + OFF_BAR, &g_flags.kvcnt[(g + 8 * pr) * 8], 16u * epoch);
    }
    __syncwarp();
    const float4* src = reinterpret_cast<const float4*>(g_kv + (size_t)(2 * g + 16 * pr) * 64 * KVW);
#pragma unroll 1
    for (int ib = 0; ib < 3; ib++) {
      float4 u[7];
#pragma unroll
      for (int i = 0; i < 7; i++) u[i] = __ldcg(src + min((ib * 7 + i) * 64 + h, 1279));
#pragma unroll
      for (int i = 0; i < 7; i++) {
        const int idx = min((ib * 7 + i) * 64 + h, 1279);
        const int f2 = idx / 10, j = idx - f2 * 10;
        const uint32_t dst = sbase + OFF_V + pr * 10240 + (f2 >> 3) * 640 + (j >> 1) * 128 + (f2 & 7) * 16 + (j & 1) * 8;
        asm volatile("st.shared.v2.b32 [%0], {%1, %2};" ::"r"(dst), "r"(pack_bf16(u[i].x, u[i].y)), "r"(pack_bf16(u[i].z, u[i].w)) : "memory");
      }
    }
    fence_async_smem();
    __syncwarp();
    if ((h & 31) == 0) mbar_arrive(sbase + OFF_BAR + B_KVX + 8 * pr);
  }
}

__device__ __forceinline__ void store_agent(const Params& prm, uint32_t sbase, int g, int rb, unsigned epoch) {
  const uint32_t bars = sbase + OFF_BAR;
  wait_ge(bars, &g_flags.zero_cnt, 128u * epoch);
  fence_async_global();
#pragma unroll 1
  for (int j = 0; j < 6; j++) {
    mbar_wait_long(bars + B_JOB + 8 * j, 0);
    unsigned* flag;
    if (j < 2) {
      const int G = g + 8 * j;
#pragma unroll 1
      for (int u = 0; u < 16; u++) {
        tma_store_4d(&prm.tmHTs, sbase + OFF_PHI + (u & 7) * 2048 + (u >> 3) * 32768, 0, (u >> 3) * 1024 + 64 * G + (u & 3) * 16, (u >> 2) & 1, rb);
        __nanosleep(50);
      }
      flag = &g_flags.hcnt[rb * 8];
    } else if (j < 4) {
      const int hp = g + 8 * (j - 2);
#pragma unroll 1
      for (int u = 0; u < 10; u++) {
        const uint32_t o = u * 2048;
        const uint32_t src = sbase + OFF_V + o;
        bulk_reduce_f32(g_kv + (size_t)(2 * hp) * 64 * KVW + o / 4, src, 2048);
        if (j == 2) __nanosleep(50);
      }
      flag = &g_flags.kvcnt[hp * 8];
    } else {
      tma_store_3d(&prm.tmO, sbase + OFF_PHI + (j - 4) * 16384, 0, 0, rb * 16 + g + 8 * (j - 4));
      flag = &g_flags.ocnt[(2 * rb + (j - 4)) * 8];
    }
    bulk_commit();
    if (j != 4) {
      bulk_wait_read();
      mbar_arrive(bars + B_EBF + 8 * (j < 4 ? j : 4));
    }
    bulk_wait_all();
    red_relaxed_add(flag, 1);
  }
}

constexpr int OST = 544;
__device__ __forceinline__ void stage_half(const float (&a)[64], uint32_t wbuf) {
  const int lane = threadIdx.x & 31, q = lane & 3, r8 = lane >> 2;
#pragma unroll
  for (int j = 0; j < 16; j++) {
    asm volatile("st.shared.v2.f32 [%0], {%1, %2};" ::"r"(wbuf + r8 * OST + j * 32 + q * 8), "f"(a[4 * j]), "f"(a[4 * j + 1]) : "memory");
    asm volatile("st.shared.v2.f32 [%0], {%1, %2};" ::"r"(wbuf + (r8 + 8) * OST + j * 32 + q * 8), "f"(a[4 * j + 2]), "f"(a[4 * j + 3]) : "memory");
  }
  __syncwarp();
}
__device__ __forceinline__ void store_y(float (&acc0)[64], const float (&acc1)[64], uint32_t wbuf, const Params& prm, int rb, int g) {
  const int lane = threadIdx.x & 31, w = (threadIdx.x & 127) >> 5;
  const uint2 dk = __ldg(reinterpret_cast<const uint2*>(prm.dskip + 128 * g) + lane);
#pragma unroll 1
  for (int half = 0; half < 2; half++) {
    const int m0 = 64 * half + 16 * w;
    const int t0 = rb * 128 + 32 * ((m0 >> 3) & 3) + 8 * (m0 >> 5);
    uint2 xs[16];
#pragma unroll
    for (int r = 0; r < 16; r++)
      xs[r] = __ldg(reinterpret_cast<const uint2*>(prm.xB + (size_t)(t0 + (r & 7) + (r >> 3) * 32) * DM + 128 * g) + lane);
    stage_half(acc0, wbuf);
    float* dst = prm.out + (size_t)t0 * 2048 + 1024 + 128 * g + 4 * lane;
#pragma unroll
    for (int r = 0; r < 16; r++) {
      float4 v = lds128(wbuf + r * OST + lane * 16);
      const float2 s0 = __bfloat1622float2(__hmul2(*reinterpret_cast<const __nv_bfloat162*>(&xs[r].x), *reinterpret_cast<const __nv_bfloat162*>(&dk.x)));
      const float2 s1 = __bfloat1622float2(__hmul2(*reinterpret_cast<const __nv_bfloat162*>(&xs[r].y), *reinterpret_cast<const __nv_bfloat162*>(&dk.y)));
      v.x += s0.x; v.y += s0.y; v.z += s1.x; v.w += s1.y;
      __stcs(reinterpret_cast<float4*>(dst + (size_t)((r & 7) + (r >> 3) * 32) * 2048), v);
    }
    __syncwarp();
#pragma unroll
    for (int i = 0; i < 64; i++) acc0[i] = acc1[i];
  }
}
__device__ __forceinline__ void drain_out(uint32_t wbuf, float* dst  ) {
  const int lane = threadIdx.x & 31;
#pragma unroll
  for (int r = 0; r < 16; r++) {
    const float4 v = lds128(wbuf + r * OST + lane * 16);
    const uint32_t p0 = pack_bf16(v.x, v.y), p1 = pack_bf16(v.z, v.w);
    __stcs(reinterpret_cast<float4*>(dst + (size_t)r * 2048) + lane,
           make_float4(__uint_as_float(p0 << 16), __uint_as_float(p0 & 0xffff0000u), __uint_as_float(p1 << 16), __uint_as_float(p1 & 0xffff0000u)));
  }
}

__global__ void __launch_bounds__(384, 1) fused_kernel(const __grid_constant__ Params prm) {
  extern __shared__ uint8_t smem_raw[];
  const uint32_t sbase = (smem_u32(smem_raw) + 1023) & ~1023u;
  const uint32_t bars = sbase + OFF_BAR;
  const int tid = threadIdx.x, wg = __shfl_sync(0xffffffffu, tid >> 7, 0);
  const int cl = blockIdx.x >> 1, rank = blockIdx.x & 1;
  const int g = cl >> 3, rb = 2 * (cl & 7) + rank;

  if (tid == 0) {
    for (int s = 0; s < STAGES; s++) { mbar_init(bars + 8 * s, 1);
      mbar_init(bars + B_EMPTY + 8 * s, 8);
    }
    mbar_init(bars + B_ORD, 1); mbar_init(bars + B_ORD + 8, 1); mbar_init(bars + B_WPHI, 1); mbar_init(bars + B_EPOCH, 1); mbar_init(bars + B_KVX, 2); mbar_init(bars + B_KVX + 8, 2);
    for (int j = 0; j < 6; j++) mbar_init(bars + B_JOB + 8 * j, 1);
    mbar_init(bars + B_PARAM, 2); mbar_init(bars + B_EBA, 1); mbar_init(bars + B_EBA + 8, 1);
    for (int j = 0; j < 5; j++) mbar_init(bars + B_EBF + 8 * j, 1);
    asm volatile("st.shared.u32 [%0], %1;" ::"r"(bars + B_DEAD), "r"(0u) : "memory");
    asm volatile("fence.mbarrier_init.release.cluster;" ::: "memory");
    asm volatile("fence.proxy.async.shared::cta;" ::: "memory");
#pragma unroll 1
    for (int kb = 0; kb < STAGES; kb++) {
      const uint32_t full = bars + 8 * kb, sw = sbase + kb * STAGE_BYTES;
      mbar_expect_tx(full, STAGE_BYTES);
      tma_5d(sw + 16384, &prm.tmXB, kb * 64, 0, 0, 0, rb, full);
      tma_2d(sw, &prm.tmBre, kb * 64, 64 * g, full);
      tma_2d(sw + 8192, &prm.tmBim, kb * 64, 64 * g, full);
    }
  } else if (tid == 32) {
    prefetch_tm(&prm.tmXB); prefetch_tm(rank ? &prm.tmBim : &prm.tmBre); prefetch_tm(&prm.tmWphi);
    prefetch_tm(&prm.tmXA); prefetch_tm(&prm.tmWqkv); prefetch_tm(&prm.tmHT);
    prefetch_tm(&prm.tmCre); prefetch_tm(&prm.tmCim); prefetch_tm(&prm.tmO); prefetch_tm(&prm.tmWo);
  } else if (tid >= 64 && tid < 128) {
    asm volatile("st.shared.v4.b32 [%0], {%1, %2, %2, %2};" ::"r"(sbase + OFF_ONES + (tid - 64) * 16), "r"(0x00003F80u), "r"(0u) : "memory");
    fence_async_smem();
  }
  __syncthreads();
  asm volatile("barrier.cluster.arrive.relaxed.aligned;\nbarrier.cluster.wait.acquire.aligned;" ::: "memory");

  if (wg == 0) {
    reg_dealloc<56>();
    const int warp = __shfl_sync(0xffffffffu, tid >> 5, 0), lane = tid & 31;
    if (warp == 0) {
      const bool leader = elect_one();
      if (leader) {
        mbar_expect_tx(bars + B_WPHI, 8192);
        tma_2d(sbase + OFF_WPHI, &prm.tmWphi, 0, 64 * g, bars + B_WPHI);
        tma_2d(sbase + OFF_WPHI + 4096, &prm.tmWphi, 0, 64 * g + 512, bars + B_WPHI);
      }
      int stage = 0;
      uint32_t phase = 0;
      unsigned epoch = 0;
      auto run = [&](auto kind, const CUtensorMap* tw, int w0, const CUtensorMap* tx, int kb0, int kb1) {
        constexpr int KIND = decltype(kind)::value;
#pragma unroll 1
        for (int kb = kb0; kb < kb1; kb++) {
          mbar_wait(bars + B_EMPTY + 8 * stage, phase);

          if (leader) {
            const uint32_t full = bars + 8 * stage;
            const uint32_t sw = sbase + stage * STAGE_BYTES;
            mbar_expect_tx(full, STAGE_BYTES);
            if (KIND == 0) {
              tma_2d_mc(sw + rank * 8192, tw, kb * 64, w0, full);
              tma_5d(sw + 16384, tx, kb * 64, 0, 0, 0, rb, full);
            } else if (KIND == 1) {
              tma_2d_mc(sw + rank * 8192, tw, w0, kb * 64, full);
              tma_2d(sw + 16384, tx, kb * 64, rb * 128, full);
            } else if (KIND == 3) {
              tma_2d_mc(sw + rank * 8192, tw, w0, kb * 64, full);
              tma_3d(sw + 16384, tx, 0, 0, rb * 16 + kb, full);
            } else {
              tma_2d_mc(sw + rank * 8192, tw, (kb & 15) * 64, w0, full);
              tma_4d(sw + 16384, tx, 0, kb * 64, 0, rb, full);
            }
          }
          if (++stage == STAGES) { stage = 0; phase ^= 1; }
        }
      };
      using K0 = std::integral_constant<int, 0>;
      using K1 = std::integral_constant<int, 1>;
      using K2 = std::integral_constant<int, 2>;
#pragma unroll 1
      for (int i = 0; i < 2; i++) run(K0{}, rank ? &prm.tmBim : &prm.tmBre, 64 * (g + 8 * i), &prm.tmXB, i == 0 ? STAGES : 0, 16);
#pragma unroll 1
      for (int i = 0; i < 3; i++)
        run(K1{}, &prm.tmWqkv, i < 2 ? 1024 + rank * 1024 + 64 * (g + 8 * i) : 64 * (g + 8 * rank), &prm.tmXA, 0, 16);
      mbar_wait(bars + B_EPOCH, 0);
      asm volatile("ld.shared.u32 %0, [%1];" : "=r"(epoch) : "r"(bars + B_EPOCHV) : "memory");
      wait_ge(bars, &g_flags.hcnt[rb * 8], 16u * epoch);
      fence_async_global();
#pragma unroll 1
      for (int i = 0; i < 2; i++) run(K2{}, i ? &prm.tmCim : &prm.tmCre, 128 * g + 64 * rank, &prm.tmHT, 16 * i, 16 * i + 16);
#pragma unroll 1
      for (int i = 0; i < 2; i++) {
        wait_ge(bars, &g_flags.ocnt[(2 * rb + i) * 8], 8u * epoch);
        fence_async_global();
        run(std::integral_constant<int, 3>{}, &prm.tmWo, 128 * g + 64 * rank, &prm.tmO, 8 * i, 8 * i + 8);
      }
    } else if (warp == 1) {
      unsigned epoch = 0;
      if (lane == 0) {
        epoch = (atomicAdd(&g_flags.ticket, 1u) >> 7) + 1u;
        asm volatile("st.shared.u32 [%0], %1;" ::"r"(bars + B_EPOCHV), "r"(epoch) : "memory");
        mbar_arrive(bars + B_EPOCH);
      }
      uint4* z = reinterpret_cast<uint4*>(g_kv) + blockIdx.x * 160;
#pragma unroll
      for (int i = 0; i < 5; i++) __stcg(z + i * 32 + lane, make_uint4(0, 0, 0, 0));
      __syncwarp();
      if (lane == 0) {
        red_release_add(&g_flags.zero_cnt, 1);
        store_agent(prm, sbase, g, rb, epoch);
      }
    } else {
#pragma unroll 1
      for (int c = 0; c < 2; c++) {
        const int ch = tid - 64, p = 64 * (g + 8 * c) + ch;
        chan_params(__bfloat162float(prm.lam_re[p]), __bfloat162float(prm.lam_im[p]), __bfloat162float(prm.log_dt[p]),
                    sbase + OFF_PHI + 16384 + (c * 64 + ch) * PSTRIDE);
      }
      __syncwarp();
      if (lane == 0) mbar_arrive(bars + B_PARAM);
      unsigned epoch;
      mbar_wait(bars + B_EPOCH, 0);
      asm volatile("ld.shared.u32 %0, [%1];" : "=r"(epoch) : "r"(bars + B_EPOCHV) : "memory");
      helper_kv(sbase, g, epoch);
    }
    __syncwarp();
    asm volatile("barrier.cluster.arrive.relaxed.aligned;\nbarrier.cluster.wait.aligned;" ::: "memory");
  } else {
    reg_alloc<224>();
    const int cw = wg - 1;
    const int t = tid & 127, lane = t & 31, w = t >> 5, r8 = lane >> 2;
    float acc0[64], acc1[64];
    unsigned epoch;
    {
      const int G = g + 8 * cw;
      ChanParams cp[2];
      const uint32_t ptab = sbase + OFF_PHI + 16384 + (cw * 64 + 16 * w + r8) * PSTRIDE;
      if (cw == 1) {
        mbar_wait(bars + B_PARAM, 0);
#pragma unroll
        for (int c = 0; c < 2; c++) cp[c] = load_params(ptab + 8 * c * PSTRIDE, lane & 3);
      }
      mainloop<0>(acc0, acc1, 16 * cw, 16, sbase, cw, cw ^ 1);
      if (cw == 0) {
        mbar_wait(bars + B_PARAM, 0);
#pragma unroll
        for (int c = 0; c < 2; c++) cp[c] = load_params(ptab + 8 * c * PSTRIDE, lane & 3);
      }
      mbar_wait(bars + B_EPOCH, 0);
      asm volatile("ld.shared.u32 %0, [%1];" : "=r"(epoch) : "r"(bars + B_EPOCHV) : "memory");
      epi_bu(acc0, acc1, cp, sbase, G, rb, cw, epoch);
    }
#pragma unroll 1
    for (int step = 0; step < 3; step++) {
      const int it0 = cw ? 48 : (step == 0 ? 32 : (step == 1 ? 64 : 112));
      mainloop<1>(acc0, acc1, it0, 16, sbase, cw, cw ? 1 : (step & 1));
      if (step == 2) {
        stage_half(acc1, sbase + (4 + w) * 16 * OST);
        asm volatile("bar.arrive 3, 256;" ::: "memory");
        stage_half(acc0, sbase + w * 16 * OST);
        drain_out(sbase + w * 16 * OST, prm.out + (size_t)(rb * 128 + 16 * w) * 2048 + 128 * g);
        break;
      }
      mbar_wait(bars + B_WPHI, 0);
      if (cw == 1) {
        mbar_wait(bars + B_EBA, 0);
      } else if (step == 1) {
        mbar_wait(bars + B_EBA + 8, 0);
      }
      epi_attn(acc0, acc1, sbase, cw, step == 1);
      if (cw == 1) break;
    }
    if (cw == 1) {
      mainloop<2>(acc0, acc1, 80, 32, sbase, 1, 0);
      mbar_wait(bars + B_EBF + 32, 0);
      store_y(acc0, acc1, sbase + OFF_EB + w * 16 * OST, prm, rb, g);
      asm volatile("bar.sync 3, 256;" ::: "memory");
      drain_out(sbase + (4 + w) * 16 * OST, prm.out + (size_t)(rb * 128 + 64 + 16 * w) * 2048 + 128 * g);
    }
    asm volatile("barrier.cluster.arrive.relaxed.aligned;\nbarrier.cluster.wait.aligned;" ::: "memory");
  }
}

typedef CUresult (*PFN_encodeTiled)(CUtensorMap*, CUtensorMapDataType, cuuint32_t, void*, const cuuint64_t*, const cuuint64_t*,
                                    const cuuint32_t*, const cuuint32_t*, CUtensorMapInterleave, CUtensorMapSwizzle,
                                    CUtensorMapL2promotion, CUtensorMapFloatOOBfill);

bool make_tm(PFN_encodeTiled enc, CUtensorMap* tm, const void* base, int rank, const uint64_t* dims, const uint64_t* strides,
             const uint32_t* box, CUtensorMapSwizzle sw) {
  cuuint64_t gd[5], gs[5];
  cuuint32_t bx[5], es[5];
  for (int i = 0; i < rank; i++) { gd[i] = dims[i]; bx[i] = box[i]; es[i] = 1; }
  for (int i = 0; i + 1 < rank; i++) gs[i] = strides[i];
  return enc(tm, CU_TENSOR_MAP_DATA_TYPE_BFLOAT16, rank, const_cast<void*>(base), gd, gs, bx, es, CU_TENSOR_MAP_INTERLEAVE_NONE, sw,
             CU_TENSOR_MAP_L2_PROMOTION_L2_128B, CU_TENSOR_MAP_FLOAT_OOB_FILL_NONE) == CUDA_SUCCESS;
}
bool make_tm2(PFN_encodeTiled enc, CUtensorMap* tm, const void* base, uint64_t inner, uint64_t outer, uint32_t b0, uint32_t b1,
              CUtensorMapSwizzle sw = CU_TENSOR_MAP_SWIZZLE_128B) {
  const uint64_t dims[2] = {inner, outer}, str[1] = {inner * 2};
  const uint32_t box[2] = {b0, b1};
  return make_tm(enc, tm, base, 2, dims, str, box, sw);
}

}

extern "C" void kernel_launch(void* const* d_in, const int* in_sizes, int n_in, void* d_out, int out_size) {
  (void)in_sizes; (void)n_in; (void)out_size;
  static PFN_encodeTiled enc = nullptr;
  static void *pHT = nullptr, *pO = nullptr;
  if (!enc) {
    void* fn = nullptr;
    cudaDriverEntryPointQueryResult qr;
    if (cudaGetDriverEntryPoint("cuTensorMapEncodeTiled", &fn, cudaEnableDefault, &qr) != cudaSuccess || !fn) return;
    enc = (PFN_encodeTiled)fn;
    cudaFuncSetAttribute(fused_kernel, cudaFuncAttributeMaxDynamicSharedMemorySize, SMEM_BYTES);
    cudaGetSymbolAddress(&pHT, g_HT);
    cudaGetSymbolAddress(&pO, g_O);
  }
  Params prm;
  bool ok = true;
  {
    const uint64_t dims[5] = {1024, 2, 4, 16, 16}, str[4] = {2048, 65536, 4096, 262144};
    const uint32_t box[5] = {64, 2, 4, 16, 1};
    ok &= make_tm(enc, &prm.tmXB, d_in[4], 5, dims, str, box, CU_TENSOR_MAP_SWIZZLE_128B);
  }
  ok &= make_tm2(enc, &prm.tmBre, d_in[7], 1024, 1024, 64, 64);
  ok &= make_tm2(enc, &prm.tmBim, d_in[8], 1024, 1024, 64, 64);
  ok &= make_tm2(enc, &prm.tmXA, d_in[0], 1024, 2048, 64, 128);
  ok &= make_tm2(enc, &prm.tmWqkv, d_in[1], 3072, 1024, 64, 64);
  ok &= make_tm2(enc, &prm.tmWphi, d_in[2], 32, 1024, 32, 64, CU_TENSOR_MAP_SWIZZLE_64B);
  {
    const uint64_t dims[4] = {64, 2048, 2, 16}, str[3] = {256, 128, 524288};
    const uint32_t box[4] = {64, 64, 2, 1}, boxs[4] = {64, 16, 1, 1};
    ok &= make_tm(enc, &prm.tmHT, pHT, 4, dims, str, box, CU_TENSOR_MAP_SWIZZLE_128B);
    ok &= make_tm(enc, &prm.tmHTs, pHT, 4, dims, str, boxs, CU_TENSOR_MAP_SWIZZLE_128B);
  }
  ok &= make_tm2(enc, &prm.tmCre, d_in[9], 1024, 1024, 64, 64);
  ok &= make_tm2(enc, &prm.tmCim, d_in[10], 1024, 1024, 64, 64);
  {
    const uint64_t dims[3] = {64, 128, 256}, str[2] = {128, 16384};
    const uint32_t box[3] = {64, 128, 1};
    ok &= make_tm(enc, &prm.tmO, pO, 3, dims, str, box, CU_TENSOR_MAP_SWIZZLE_128B);
  }
  ok &= make_tm2(enc, &prm.tmWo, d_in[3], 1024, 1024, 64, 64);
  if (!ok) return;
  prm.xB = (const __nv_bfloat16*)d_in[4];
  prm.lam_re = (const __nv_bfloat16*)d_in[5];
  prm.lam_im = (const __nv_bfloat16*)d_in[6];
  prm.log_dt = (const __nv_bfloat16*)d_in[11];
  prm.dskip = (const __nv_bfloat16*)d_in[12];
  prm.out = (float*)d_out;

  cudaLaunchConfig_t cfg = {};
  cfg.gridDim = dim3(128);
  cfg.blockDim = dim3(384);
  cfg.dynamicSmemBytes = SMEM_BYTES;
  cfg.stream = cudaStreamPerThread;
  cudaLaunchAttribute attr[1];
  attr[0].id = cudaLaunchAttributeClusterDimension;
  attr[0].val.clusterDim.x = 2; attr[0].val.clusterDim.y = 1; attr[0].val.clusterDim.z = 1;
  cfg.attrs = attr;
  cfg.numAttrs = 1;
  cudaLaunchKernelEx(&cfg, fused_kernel, prm);
}
```
